```python
import torch

def _softmax(x, axis=-1):
    return torch.softmax(x, dim=axis)
def _gelu(x):
    return torch.nn.functional.gelu(x, approximate="tanh")
def _silu(x):
    return torch.nn.functional.silu(x)
def _sigmoid(x):
    return torch.sigmoid(x)
def _layernorm(x, axis=-1, eps=1e-5):
    m = x.mean(dim=axis, keepdim=True)
    v = x.var(dim=axis, keepdim=True, unbiased=False)
    return (x - m) / torch.sqrt(v + eps)
def _scatter_add(tgt, idx, src, axis=0):
    return tgt.clone().index_add_(axis, idx, src)
def _segment_sum(src, seg, n):
    out = torch.zeros((n,) + src.shape[1:], dtype=src.dtype)
    return out.index_add_(0, seg, src)
def _pad(x, pw):
    flat = tuple(v for pair in reversed(pw) for v in pair)
    return torch.nn.functional.pad(x, flat)

kernel_name = 'parallel_sum__sliding_block_cached__dense_activation_mish__decode'

def setup_inputs():

    _w = (lambda a: (lambda t: t.to(torch.bfloat16) if t.is_floating_point() else t)(torch.as_tensor(a)))
    def _A_setup():
        B, Sq, D = 2, 1, 512
        Hq, Hkv, Sk, Dh = 32, 8, 8192, 128
        assert Hq % Hkv == 0, (Hq, Hkv)
        return {
            "x": _w((lambda *s: torch.randn(*s, dtype=torch.bfloat16) * 0.05)(B, Sq, D)),
            "k_cache": _w((lambda *s: torch.randn(*s, dtype=torch.bfloat16) * 1.6)(B, Hkv, Sk, Dh)),
            "v_cache": _w((lambda *s: torch.randn(*s, dtype=torch.bfloat16) * 0.4)(B, Hkv, Sk, Dh)),
            "wq": _w((lambda *s: torch.randn(*s, dtype=torch.bfloat16) * 1.6)(D, Hq * Dh) * (D ** -0.5)),
            "wo": _w((lambda *s: torch.randn(*s, dtype=torch.bfloat16) * 0.4)(Hq * Dh, D) * ((Hq * Dh) ** -0.5)),
        }
    _A_in = _A_setup()

    def _B_setup():
        B, S, D, F = 2, 1, 512, 1792
        return {
            "x": _w((lambda *s: torch.randn(*s, dtype=torch.bfloat16) * 0.05)(B, S, D)),
            "w1": _w((lambda *s: torch.randn(*s, dtype=torch.bfloat16) * 0.8)(D, F) * (D ** -0.5)),
            "b1": _w((lambda *s: torch.randn(*s, dtype=torch.bfloat16) * 0.2)(F)),
            "w2": _w((lambda *s: torch.randn(*s, dtype=torch.bfloat16) * 0.1)(F, D) * (F ** -0.5)),
        }
    _B_in = _B_setup()

    return {
        "A_x": _A_in["x"],
        "A_k_cache": _A_in["k_cache"],
        "A_v_cache": _A_in["v_cache"],
        "A_wq": _A_in["wq"],
        "A_wo": _A_in["wo"],
        "B_x": _B_in["x"],
        "B_w1": _B_in["w1"],
        "B_b1": _B_in["b1"],
        "B_w2": _B_in["w2"],
    }

def reference(A_x, A_k_cache, A_v_cache, A_wq, A_wo, B_x, B_w1, B_b1, B_w2):
    def _A_ref(x, k_cache, v_cache, wq, wo):
        B, Sq, D = x.shape
        Hq, Dh = 32, 128
        Hkv, Sk = k_cache.shape[1], k_cache.shape[2]
        W = min(4096, max(256, Sk // 4))
        rep = Hq // Hkv
        q = (lambda x, *d: x.permute(*d))((x @ wq).reshape(B, Sq, Hq, Dh), 0, 2, 1, 3)
        k = (lambda x, n, axis: torch.repeat_interleave(x, n, dim=axis))(k_cache[:, :, Sk - W:, :], rep, axis=1)
        v = (lambda x, n, axis: torch.repeat_interleave(x, n, dim=axis))(v_cache[:, :, Sk - W:, :], rep, axis=1)
        scores = torch.einsum("bhqd,bhkd->bhqk", q, k) * (Dh ** -0.5)
        p = _softmax(scores, axis=-1)
        o = torch.einsum("bhqk,bhkd->bhqd", p, v)
        return (lambda x, *d: x.permute(*d))(o, 0, 2, 1, 3).reshape(B, Sq, Hq * Dh) @ wo

    def _B_ref(x, w1, b1, w2):
        h = torch.einsum("bsd,df->bsf", x, w1) + b1
        sp = torch.log1p(torch.exp(-torch.abs(h))) + torch.where(h > 0, h, torch.zeros_like(h))
        act = h * torch.tanh(sp)
        return torch.einsum("bsf,fd->bsd", act, w2)

    x = A_x
    xn = _layernorm(x, axis=-1)
    return x + _A_ref(xn, A_k_cache, A_v_cache, A_wq, A_wo) + _B_ref(xn, B_w1, B_b1, B_w2)
```

```cpp
#include <cuda_runtime.h>
#include <cuda_bf16.h>
#include <cuda.h>
#include <stdint.h>

namespace {

constexpr int NCTA     = 128;
constexpr int CLUSTER  = 8;
constexpr int NFFN     = 112;
constexpr int NTHREADS = 352;
constexpr int SPIN_LIMIT = 1 << 22;
#define PACE 640
#define LEAD8 48
#define WMIN 4
#define BGATE 0
#define WB 4
#define LEADB8 16
#define PUTMODE 1
#define POLLSLEEP 0
#define POLLGATE 0
#define QPROMO CU_TENSOR_MAP_L2_PROMOTION_L2_128B
#define WPROMO CU_TENSOR_MAP_L2_PROMOTION_NONE

__device__ __align__(128) unsigned g_ino[NCTA * 512];
__device__ __align__(128) unsigned g_ina[NCTA * 256];

constexpr int NSLOT   = 12;
constexpr int NSTAGE  = 32;
constexpr int ST_K = 8, ST_V = 16, ST_W1 = 24, ST_WO = 26, ST_W2 = 30;
constexpr int SM_QP   = NSLOT * 8192;
constexpr int SM_R4   = SM_QP;
constexpr int SM_Q    = SM_QP + 2048;
constexpr int SM_INO  = SM_Q + 1024;
constexpr int SM_INF  = SM_INO + 2048;
constexpr int SM_P    = SM_INF + 1024;
constexpr int SM_ML   = SM_P + 2048;
constexpr int SM_WMAX = SM_ML + 64;
constexpr int SM_WSUM = SM_WMAX + 128;
constexpr int SM_XN   = SM_WSUM + 128;
constexpr int SM_BAR  = SM_XN + 256;
constexpr int BAR_FULL = 0, BAR_EMPTY = 12, BAR_QP = 24, BAR_Q = 25, BAR_ML = 26, BAR_O = 27, BAR_F = 28, BAR_R4 = 29, BAR_XN = 30;
constexpr int SM_TOTAL = SM_BAR + 32 * 8 + 1024;

#define TS(i) do { } while (0)

__device__ __forceinline__ void mbar_init(uint32_t bar, uint32_t cnt) {
    asm volatile("mbarrier.init.shared::cta.b64 [%0], %1;" :: "r"(bar), "r"(cnt) : "memory");
}
__device__ __forceinline__ void mbar_expect_tx(uint32_t bar, uint32_t bytes) {
    asm volatile("mbarrier.arrive.expect_tx.shared::cta.b64 _, [%0], %1;" :: "r"(bar), "r"(bytes) : "memory");
}
__device__ __forceinline__ void mbar_arrive(uint32_t bar, uint32_t cnt) {
    asm volatile("mbarrier.arrive.shared::cta.b64 _, [%0], %1;" :: "r"(bar), "r"(cnt) : "memory");
}
__device__ __forceinline__ bool mbar_try(uint32_t bar, uint32_t parity) {
    uint32_t ok;
    asm volatile("{\n .reg .pred p;\n mbarrier.try_wait.parity.shared::cta.b64 p, [%1], %2;\n selp.u32 %0, 1, 0, p;\n}"
                 : "=r"(ok) : "r"(bar), "r"(parity) : "memory");
    return ok != 0;
}
__device__ __forceinline__ bool mbar_test(uint32_t bar, uint32_t parity) {
    uint32_t ok;
    asm volatile("{\n .reg .pred p;\n mbarrier.test_wait.parity.shared::cta.b64 p, [%1], %2;\n selp.u32 %0, 1, 0, p;\n}"
                 : "=r"(ok) : "r"(bar), "r"(parity) : "memory");
    return ok != 0;
}
__device__ __forceinline__ void mbar_wait(uint32_t bar, uint32_t parity) {
    if (mbar_try(bar, parity)) return;
    for (int it = 0; it < SPIN_LIMIT; ++it)
        if (mbar_try(bar, parity)) return;
}
__device__ __forceinline__ void bulk_load(uint32_t dst, const void* src, uint32_t bytes, uint32_t bar) {
    asm volatile("cp.async.bulk.shared::cluster.global.mbarrier::complete_tx::bytes [%0], [%1], %2, [%3];"
                 :: "r"(dst), "l"(src), "r"(bytes), "r"(bar) : "memory");
}
__device__ __forceinline__ void tma3d(uint32_t dst, const CUtensorMap* map, int c1, int c2, uint32_t bar) {
    asm volatile("cp.async.bulk.tensor.3d.shared::cluster.global.mbarrier::complete_tx::bytes [%0], [%1, {%3, %4, %5}], [%2];"
                 :: "r"(dst), "l"(map), "r"(bar), "r"(0), "r"(c1), "r"(c2) : "memory");
}
__device__ __forceinline__ void tma2d(uint32_t dst, const CUtensorMap* map, int c0, int c1, uint32_t bar) {
    asm volatile("cp.async.bulk.tensor.2d.shared::cluster.global.mbarrier::complete_tx::bytes [%0], [%1, {%3, %4}], [%2];"
                 :: "r"(dst), "l"(map), "r"(bar), "r"(c0), "r"(c1) : "memory");
}
__device__ __forceinline__ uint32_t mapa(uint32_t a, uint32_t rank) {
    uint32_t d;
    asm("mapa.shared::cluster.u32 %0, %1, %2;" : "=r"(d) : "r"(a), "r"(rank));
    return d;
}
__device__ __forceinline__ void st_async1(uint32_t dst, uint32_t v, uint32_t bar) {
    asm volatile("st.async.shared::cluster.mbarrier::complete_tx::bytes.b32 [%0], %1, [%2];"
                 :: "r"(dst), "r"(v), "r"(bar) : "memory");
}
__device__ __forceinline__ void st_async2(uint32_t dst, float a, float b, uint32_t bar) {
    asm volatile("st.async.shared::cluster.mbarrier::complete_tx::bytes.v2.f32 [%0], {%1,%2}, [%3];"
                 :: "r"(dst), "f"(a), "f"(b), "r"(bar) : "memory");
}
__device__ __forceinline__ void st_async4(uint32_t dst, float a, float b, float c, float d, uint32_t bar) {
    asm volatile("st.async.shared::cluster.mbarrier::complete_tx::bytes.v4.f32 [%0], {%1,%2,%3,%4}, [%5];"
                 :: "r"(dst), "f"(a), "f"(b), "f"(c), "f"(d), "r"(bar) : "memory");
}
__device__ __forceinline__ void put16(void* p, unsigned a, unsigned b, unsigned c, unsigned d) {
    asm volatile("{\n .reg .b64 lo, hi;\n mov.b64 lo, {%1,%2};\n mov.b64 hi, {%3,%4};\n"
                 " red.relaxed.gpu.global.or.b64 [%0], lo;\n red.relaxed.gpu.global.or.b64 [%0+8], hi;\n}"
                 :: "l"(p), "r"(a), "r"(b), "r"(c), "r"(d) : "memory");
}
__device__ __forceinline__ void clear16(void* p) {
    asm volatile("st.relaxed.gpu.global.v4.u32 [%0], {%1,%1,%1,%1};" :: "l"(p), "r"(0u) : "memory");
}
__device__ __forceinline__ void clear8(void* p) {
    asm volatile("st.relaxed.gpu.global.v2.u32 [%0], {%1,%1};" :: "l"(p), "r"(0u) : "memory");
}
__device__ __forceinline__ void take_round(uint4& a, uint4& b, uint2& c, uint2& d, void* p16, void* p8, int m) {
    asm volatile("{\n .reg .pred p0, p1, p2, p3;\n .reg .b32 t;\n"
                 " and.b32 t, %14, 1;\n setp.ne.s32 p0, t, 0;\n and.b32 t, %14, 2;\n setp.ne.s32 p1, t, 0;\n"
                 " and.b32 t, %14, 4;\n setp.ne.s32 p2, t, 0;\n and.b32 t, %14, 8;\n setp.ne.s32 p3, t, 0;\n"
                 " @p0 ld.relaxed.gpu.global.v4.u32 {%0,%1,%2,%3}, [%12];\n"
                 " @p1 ld.relaxed.gpu.global.v4.u32 {%4,%5,%6,%7}, [%12+16];\n"
                 " @p2 ld.relaxed.gpu.global.v2.u32 {%8,%9}, [%13];\n"
                 " @p3 ld.relaxed.gpu.global.v2.u32 {%10,%11}, [%13+448];\n}"
                 : "+r"(a.x), "+r"(a.y), "+r"(a.z), "+r"(a.w), "+r"(b.x), "+r"(b.y), "+r"(b.z), "+r"(b.w),
                   "+r"(c.x), "+r"(c.y), "+r"(d.x), "+r"(d.y)
                 : "l"(p16), "l"(p8), "r"(m) : "memory");
}
__device__ __forceinline__ bool nz4(const uint4& v) { return v.x != 0u && v.y != 0u && v.z != 0u && v.w != 0u; }
__device__ __forceinline__ bool nz2(const uint2& v) { return v.x != 0u && v.y != 0u; }
__device__ __forceinline__ unsigned enc(unsigned w) { return ~min(w, 0xFFFFFFFEu); }
__device__ __forceinline__ uint4 lds128(uint32_t a) {
    uint4 v;
    asm volatile("ld.shared.v4.u32 {%0,%1,%2,%3}, [%4];" : "=r"(v.x), "=r"(v.y), "=r"(v.z), "=r"(v.w) : "r"(a) : "memory");
    return v;
}
__device__ __forceinline__ float2 lds64f(uint32_t a) {
    float2 v;
    asm volatile("ld.shared.v2.f32 {%0,%1}, [%2];" : "=f"(v.x), "=f"(v.y) : "r"(a) : "memory");
    return v;
}
__device__ __forceinline__ uint32_t lds32(uint32_t a) {
    uint32_t v;
    asm volatile("ld.shared.u32 %0, [%1];" : "=r"(v) : "r"(a) : "memory");
    return v;
}
__device__ __forceinline__ void sts32(uint32_t a, uint32_t v) {
    asm volatile("st.shared.u32 [%0], %1;" :: "r"(a), "r"(v) : "memory");
}
__device__ __forceinline__ void mma16816(float (&d)[4], uint32_t a0, uint32_t a1, uint32_t a2, uint32_t a3,
                                         uint32_t b0, uint32_t b1) {
    asm volatile("mma.sync.aligned.m16n8k16.row.col.f32.bf16.bf16.f32 {%0,%1,%2,%3}, {%4,%5,%6,%7}, {%8,%9}, {%0,%1,%2,%3};"
                 : "+f"(d[0]), "+f"(d[1]), "+f"(d[2]), "+f"(d[3])
                 : "r"(a0), "r"(a1), "r"(a2), "r"(a3), "r"(b0), "r"(b1));
}
__device__ __forceinline__ void ldt_mma(float (&d)[4], uint32_t addr, uint32_t b0, uint32_t b1) {
    uint32_t a0, a1, a2, a3;
    asm volatile("ldmatrix.sync.aligned.m8n8.x4.trans.shared.b16 {%0,%1,%2,%3}, [%4];"
                 : "=r"(a0), "=r"(a1), "=r"(a2), "=r"(a3) : "r"(addr) : "memory");
    mma16816(d, a0, a1, a2, a3, b0, b1);
}
__device__ __forceinline__ uint32_t pack_bf16(float lo, float hi) {
    uint32_t r;
    asm("cvt.rn.bf16x2.f32 %0, %1, %2;" : "=r"(r) : "f"(hi), "f"(lo));
    return r;
}
__device__ __forceinline__ float bf_lo(uint32_t w) { return __uint_as_float(w << 16); }
__device__ __forceinline__ float bf_hi(uint32_t w) { return __uint_as_float(w & 0xFFFF0000u); }
__device__ __forceinline__ float ex2(float x) {
    float y;
    asm("ex2.approx.ftz.f32 %0, %1;" : "=f"(y) : "f"(x));
    return y;
}
__device__ __forceinline__ void cbar() { asm volatile("bar.sync 1, 256;" ::: "memory"); }

__host__ __device__ constexpr int cum8(int s) {
    return s <= 8 ? s * 4 : s <= 24 ? 32 + (s - 8) * 8 : s <= 26 ? 160 + (s - 24) * 7 : s <= 30 ? 174 + (s - 26) * 8 : 206 + (s - 30) * 7;
}
__device__ __forceinline__ uint32_t empty_of(int stage) { return (uint32_t)(BAR_EMPTY + stage % NSLOT) * 8u; }
__device__ __forceinline__ uint32_t slot_of(int stage) { return (uint32_t)(stage % NSLOT) * 8192u; }
__device__ __forceinline__ uint32_t full_of(int stage) { return (uint32_t)(BAR_FULL + stage % NSLOT) * 8u; }
__device__ __forceinline__ uint32_t par_of(int stage) { return (uint32_t)(stage / NSLOT) & 1u; }

__global__ void __launch_bounds__(NTHREADS, 2)
fused_decode_kernel(const __grid_constant__ CUtensorMap map_wq, const __grid_constant__ CUtensorMap map_v,
                    const __grid_constant__ CUtensorMap map_w1, const __grid_constant__ CUtensorMap map_wo,
                    const __grid_constant__ CUtensorMap map_w2,
                    const __nv_bfloat16* __restrict__ x, const __nv_bfloat16* __restrict__ kc,
                    const __nv_bfloat16* __restrict__ b1, __nv_bfloat16* __restrict__ out) {
    extern __shared__ unsigned char smem_raw[];
    const uint32_t sb = ((uint32_t)__cvta_generic_to_shared(smem_raw) + 1023u) & ~1023u;
    const uint32_t bars = sb + SM_BAR;
    const int tid = threadIdx.x, warp = tid >> 5, lane = tid & 31;
    const int cta = blockIdx.x;
    const int cl = cta >> 3, rank = cta & 7;
    const int b = cl >> 3, g = cl & 7;
    const bool ffn = cta < NFFN;
    const float SC = 0.08838834764831845f * 1.4426950408889634f;

    const int krow = cl * 8192 + 6144 + rank * 256;
    const char* ksrc = (const char*)(kc + (size_t)krow * 128);
    auto issue = [&](int s) {
        const uint32_t fb = bars + full_of(s), dst = sb + slot_of(s);
        if (!ffn && (s == ST_W1 || s == ST_W1 + 1)) {
            mbar_arrive(fb, 1);
        } else {
            mbar_expect_tx(fb, s >= ST_W2 ? 7168 : 8192);
            if (s < ST_V)        bulk_load(dst, ksrc + (s - ST_K) * 8192, 8192, fb);
            else if (s < ST_W1)  tma3d(dst, &map_v, krow + (s - ST_V) * 32, 0, fb);
            else if (s < ST_WO)  tma3d(dst, &map_w1, rank * 64 + (s - ST_W1) * 32, cl * 2, fb);
            else if (s < ST_W2)  tma2d(dst, &map_wo, cl * 32, rank * 512 + (s - ST_WO) * 128, fb);
            else                 tma2d(dst, &map_w2, cl * 32, rank * 224 + (s - ST_W2) * 112, fb);
        }
    };

    if (warp == 8) {
        const uint32_t c0 = (uint32_t)clock();
        if (lane == 0) {
            TS(0);
#pragma unroll
            for (int s = ST_K; s < NSLOT; ++s) {
                mbar_init(bars + full_of(s), 1);
                if (cum8(s) <= LEAD8) issue(s);
            }
            asm volatile("prefetch.tensormap [%0];" :: "l"(&map_v) : "memory");
            asm volatile("prefetch.tensormap [%0];" :: "l"(&map_w1) : "memory");
            asm volatile("prefetch.tensormap [%0];" :: "l"(&map_wo) : "memory");
            asm volatile("prefetch.tensormap [%0];" :: "l"(&map_w2) : "memory");
        }
        __syncthreads();
        asm volatile("barrier.cluster.arrive.relaxed.aligned;" ::: "memory");
        if (lane == 0) {
#pragma unroll
            for (int s = ST_K; s < NSTAGE; ++s) {
                if (s < NSLOT && cum8(s) <= LEAD8) continue;
                if (s < ST_WO) {
                    for (int it = 0; it < SPIN_LIMIT; ++it) {
                        if ((int)((uint32_t)clock() - c0) >= (cum8(s) - LEAD8) * PACE / 8) break;
                        if (mbar_test(bars + full_of(s - WMIN), par_of(s - WMIN))) break;
                    }
                } else if (BGATE > 0) {
                    if (s == ST_WO) {
#pragma unroll
                        for (int k = ST_V; k <= BGATE; ++k) mbar_wait(bars + full_of(k), par_of(k));
                    }
                } else {
                    if (s == ST_WO) {
#pragma unroll
                        for (int k = ST_V; k < s - WB; ++k) mbar_wait(bars + full_of(k), par_of(k));
                    }
                    for (int it = 0; it < SPIN_LIMIT; ++it) {
                        if ((int)((uint32_t)clock() - c0) >= (cum8(s) - LEADB8) * PACE / 8) break;
                        if (mbar_test(bars + full_of(s - WB), par_of(s - WB))) break;
                    }
                }
                if (s >= NSLOT) mbar_wait(bars + empty_of(s), par_of(s - NSLOT));
                issue(s);
            }
            TS(1);
        }
    } else if (warp == 10) {
        __syncthreads();
        asm volatile("barrier.cluster.arrive.relaxed.aligned;" ::: "memory");
        {
            mbar_wait(bars + BAR_ML * 8, 0);
            float wn[8];
            {
                float m[8], l[8];
#pragma unroll
                for (int s = 0; s < 8; s += 2) {
                    const uint4 t = lds128(sb + SM_ML + s * 8);
                    m[s] = __uint_as_float(t.x); l[s] = __uint_as_float(t.y);
                    m[s + 1] = __uint_as_float(t.z); l[s + 1] = __uint_as_float(t.w);
                }
                const float M = fmaxf(fmaxf(fmaxf(m[0], m[1]), fmaxf(m[2], m[3])), fmaxf(fmaxf(m[4], m[5]), fmaxf(m[6], m[7])));
                float L = 0.f;
#pragma unroll
                for (int s = 0; s < 8; ++s) { wn[s] = ex2((m[s] - M) * SC); L = fmaf(wn[s], l[s], L); }
                const float inv = 1.f / L;
#pragma unroll
                for (int s = 0; s < 8; ++s) wn[s] *= inv;
            }
            mbar_wait(bars + BAR_O * 8, 0);
            TS(9);
            float o0 = 0.f, o1 = 0.f;
#pragma unroll
            for (int s = 0; s < 8; ++s) {
                const float2 t = lds64f(sb + SM_INO + s * 256 + lane * 8);
                o0 = fmaf(wn[s], t.x, o0); o1 = fmaf(wn[s], t.y, o1);
            }
            const uint32_t ow = enc(pack_bf16(o0, o1));
            const int l0 = (lane & 1) * 16 + ((lane >> 1) & 3);
            const uint32_t w0 = __shfl_sync(0xffffffffu, ow, l0),     w1_ = __shfl_sync(0xffffffffu, ow, l0 + 4);
            const uint32_t w2_ = __shfl_sync(0xffffffffu, ow, l0 + 8), w3 = __shfl_sync(0xffffffffu, ow, l0 + 12);
            unsigned* dst = g_ino + ((lane >> 3) * 8 + g) * 512 + rank * 64 + b * 32 + (lane & 7) * 4;
#pragma unroll
            for (int k = 0; k < 4; ++k) put16(dst + k * 32 * 512, w0, w1_, w2_, w3);
            TS(3);
        }
    } else if (warp == 9) {
        const uint4 xa0 = __ldg((const uint4*)(x + lane * 16));
        const uint4 xa1 = __ldg((const uint4*)(x + lane * 16 + 8));
        const uint4 xc0 = __ldg((const uint4*)(x + 512 + lane * 16));
        const uint4 xc1 = __ldg((const uint4*)(x + 512 + lane * 16 + 8));
        const uint32_t xr0 = __ldg((const unsigned*)(x + rank * 64) + lane);
        const uint32_t xr1 = __ldg((const unsigned*)(x + 512 + rank * 64) + lane);
        const int e = (lane & 1) * 4 + ((lane >> 1) & 1) * 2 + ((lane >> 2) & 1);
        const int oidx = (e & 1) * 512 + cl * 32 + (e >> 1) * 8 + rank;
        const float xres = __bfloat162float(x[oidx]);
        float bias = 0.f;
        if (ffn) bias = __bfloat162float(b1[cta * 16 + (lane >> 1)]);
        if (lane == 0) {
            mbar_init(bars + BAR_XN * 8, 1);
            mbar_init(bars + BAR_QP * 8, 1); mbar_expect_tx(bars + BAR_QP * 8, 2048);
            mbar_init(bars + BAR_Q * 8, 1);  mbar_expect_tx(bars + BAR_Q * 8, 1024);
            mbar_init(bars + BAR_ML * 8, 1); mbar_expect_tx(bars + BAR_ML * 8, 64);
            asm volatile("fence.mbarrier_init.release.cluster;" ::: "memory");
        }
        __syncthreads();
        asm volatile("barrier.cluster.arrive.relaxed.aligned;" ::: "memory");
        {
            const uint32_t wa[8] = {xa0.x, xa0.y, xa0.z, xa0.w, xa1.x, xa1.y, xa1.z, xa1.w};
            const uint32_t wc[8] = {xc0.x, xc0.y, xc0.z, xc0.w, xc1.x, xc1.y, xc1.z, xc1.w};
            float s0 = 0.f, s1 = 0.f;
#pragma unroll
            for (int i = 0; i < 8; ++i) { s0 += bf_lo(wa[i]) + bf_hi(wa[i]); s1 += bf_lo(wc[i]) + bf_hi(wc[i]); }
#pragma unroll
            for (int o = 16; o; o >>= 1) { s0 += __shfl_xor_sync(0xffffffffu, s0, o); s1 += __shfl_xor_sync(0xffffffffu, s1, o); }
            const float m0 = s0 * (1.f / 512.f), m1 = s1 * (1.f / 512.f);
            float v0 = 0.f, v1 = 0.f;
#pragma unroll
            for (int i = 0; i < 8; ++i) {
                float d;
                d = bf_lo(wa[i]) - m0; v0 = fmaf(d, d, v0); d = bf_hi(wa[i]) - m0; v0 = fmaf(d, d, v0);
                d = bf_lo(wc[i]) - m1; v1 = fmaf(d, d, v1); d = bf_hi(wc[i]) - m1; v1 = fmaf(d, d, v1);
            }
#pragma unroll
            for (int o = 16; o; o >>= 1) { v0 += __shfl_xor_sync(0xffffffffu, v0, o); v1 += __shfl_xor_sync(0xffffffffu, v1, o); }
            const float r0 = rsqrtf(v0 * (1.f / 512.f) + 1e-5f), r1 = rsqrtf(v1 * (1.f / 512.f) + 1e-5f);
            sts32(sb + SM_XN + lane * 4,       pack_bf16((bf_lo(xr0) - m0) * r0, (bf_hi(xr0) - m0) * r0));
            sts32(sb + SM_XN + 128 + lane * 4, pack_bf16((bf_lo(xr1) - m1) * r1, (bf_hi(xr1) - m1) * r1));
            __syncwarp();
            if (lane == 0) mbar_arrive(bars + BAR_XN * 8, 1);
        }
        asm volatile("barrier.cluster.wait.acquire.aligned;" ::: "memory");
        {
            mbar_wait(bars + BAR_QP * 8, 0);
            TS(6);
            const uint32_t a = sb + SM_QP + (((2 * lane) & 7) * 8 + (lane >> 2)) * 4;
            float q0 = 0.f, q1 = 0.f;
#pragma unroll
            for (int s = 0; s < 8; ++s) {
                q0 += __uint_as_float(lds32(a + s * 256));
                q1 += __uint_as_float(lds32(a + s * 256 + 32));
            }
            const uint32_t qw = pack_bf16(q0, q1);
#pragma unroll
            for (int d = 0; d < 8; ++d)
                st_async1(mapa(sb + SM_Q + rank * 128 + lane * 4, d), qw, mapa(bars + BAR_Q * 8, d));
        }
        if (ffn) {
            mbar_wait(bars + BAR_F * 8, 0);
            TS(10);
            float h = bias;
#pragma unroll
            for (int s = 0; s < 8; ++s) h += __uint_as_float(lds32(sb + SM_INF + s * 128 + lane * 4));
            const float ee = __expf(-fabsf(h));
            const float num = h >= 0.f ? fmaf(2.f, ee, 1.f) : ee * (ee + 2.f);
            const float den = h >= 0.f ? fmaf(2.f * ee, ee, num) : num + 2.f;
            const float act = h * (num / den);
            const int src = ((lane >> 1) & 7) * 4 + (lane & 1);
            const uint32_t w = enc(pack_bf16(__shfl_sync(0xffffffffu, act, src), __shfl_sync(0xffffffffu, act, src + 2)));
            const int l0 = (lane & 1) * 4 + ((lane >> 1) & 1);
            const uint32_t w0 = __shfl_sync(0xffffffffu, w, l0),      w1_ = __shfl_sync(0xffffffffu, w, l0 + 8);
            const uint32_t w2_ = __shfl_sync(0xffffffffu, w, l0 + 2), w3 = __shfl_sync(0xffffffffu, w, l0 + 10);
            const int rc = cta / 14;
            unsigned* dst = g_ina + ((lane >> 2) * 8 + rc) * 256 + (cta - rc * 14) * 16 + (lane & 3) * 4;
            put16(dst, w0, w1_, w2_, w3);
            put16(dst + 64 * 256, w0, w1_, w2_, w3);
            TS(17);
        }
        mbar_wait(bars + BAR_R4 * 8, 0);
        TS(2);
        {
            float a0 = 0.f, a1 = 0.f, a2 = 0.f, a3 = 0.f;
#pragma unroll
            for (int i = 0; i < 4; ++i) {
                const uint4 t = lds128(sb + SM_R4 + i * 512 + lane * 16);
                a0 += __uint_as_float(t.x); a1 += __uint_as_float(t.y);
                a2 += __uint_as_float(t.z); a3 += __uint_as_float(t.w);
            }
            const bool h1 = lane & 2, h2 = lane & 4;
            float k0 = h1 ? a2 : a0, k1 = h1 ? a3 : a1;
            k0 += __shfl_xor_sync(0xffffffffu, h1 ? a0 : a2, 2);
            k1 += __shfl_xor_sync(0xffffffffu, h1 ? a1 : a3, 2);
            float r = h2 ? k1 : k0;
            r += __shfl_xor_sync(0xffffffffu, h2 ? k0 : k1, 4);
            r += __shfl_xor_sync(0xffffffffu, r, 8);
            r += __shfl_xor_sync(0xffffffffu, r, 16);
            if (lane < 8) out[oidx] = __float2bfloat16(r + xres);
        }
        TS(5);
    } else {
        const int r = lane >> 2, c = lane & 3;
        const int mi = lane >> 3, rr = lane & 7;
        if (lane == 0) {
            mbar_init(bars + full_of(warp), 1);
            mbar_expect_tx(bars + full_of(warp), 8192);
            tma2d(sb + slot_of(warp), &map_wq, g * 512 + warp * 64, rank * 64, bars + full_of(warp));
            mbar_init(bars + (BAR_EMPTY + warp) * 8, 8);
            if (warp < 4) mbar_init(bars + (BAR_EMPTY + 8 + warp) * 8, 8);
            else if (warp < 7) {
                mbar_init(bars + (BAR_O + warp - 4) * 8, 1);
                mbar_expect_tx(bars + (BAR_O + warp - 4) * 8, warp == 5 ? 1024u : 2048u);
            }
            asm volatile("fence.mbarrier_init.release.cluster;" ::: "memory");
        }
        __syncthreads();
        asm volatile("barrier.cluster.arrive.relaxed.aligned;" ::: "memory");
        const uint32_t va = sb + (warp >> 2) * 4096 + ((mi >> 1) * 8 + rr) * 128 + ((((2 * warp) & 7) + (mi & 1)) ^ rr) * 16;
        uint32_t xb[8];
        {
            mbar_wait(bars + BAR_XN * 8, 0);
#pragma unroll
            for (int i = 0; i < 8; ++i) xb[i] = r < 2 ? lds32(sb + SM_XN + r * 128 + (i * 4 + c) * 4) : 0u;
            float acc[4][4] = {};
            const uint32_t wa = sb + slot_of(warp) + ((mi >> 1) * 8 + rr) * 128;
            const uint32_t sw = (uint32_t)(((mi & 1) ^ rr) * 16);
            mbar_wait(bars + full_of(warp), 0);
#pragma unroll
            for (int ks = 0; ks < 4; ++ks)
#pragma unroll
                for (int t = 0; t < 4; ++t) ldt_mma(acc[t], wa + ks * 2048 + (sw ^ (t * 32)), xb[2 * ks], xb[2 * ks + 1]);
            __syncwarp();
            if (lane == 0) mbar_arrive(bars + empty_of(warp), 8);
            if (warp == 0) TS(11);
            asm volatile("barrier.cluster.wait.acquire.aligned;" ::: "memory");
            if (c == 0) {
                const uint32_t dst = mapa(sb + SM_QP + rank * 256 + r * 32, warp), rb = mapa(bars + BAR_QP * 8, warp);
                st_async4(dst,      b ? acc[0][1] : acc[0][0], b ? acc[0][3] : acc[0][2], b ? acc[1][1] : acc[1][0], b ? acc[1][3] : acc[1][2], rb);
                st_async4(dst + 16, b ? acc[2][1] : acc[2][0], b ? acc[2][3] : acc[2][2], b ? acc[3][1] : acc[3][0], b ? acc[3][3] : acc[3][2], rb);
            }
            if (warp == 0) TS(12);
        }
        unsigned* const ino = g_ino + cta * 512 + warp * 64 + lane * 8;
        unsigned* const ina = g_ina + cta * 256 + (warp < 7 ? warp : 0) * 16 + lane * 2;
        const bool pol = r < 2;
        const int pmask = pol ? (warp < 7 ? 15 : 3) : 0;
        auto missing = [&](const uint4& a, const uint4& b2, const uint2& c2, const uint2& d2) {
            return pmask & ((nz4(a) ? 0 : 1) | (nz4(b2) ? 0 : 2) | (nz2(c2) ? 0 : 4) | (nz2(d2) ? 0 : 8));
        };
        uint4 mo0 = make_uint4(0u, 0u, 0u, 0u), mo1 = mo0;
        uint2 ma0 = make_uint2(0u, 0u), ma1 = ma0;
        take_round(mo0, mo1, ma0, ma1, ino, ina, pmask);
        float sacc[2][4] = {};
        {
            mbar_wait(bars + BAR_Q * 8, 0);
            if (warp == 0) TS(7);
            uint4 qf[4];
#pragma unroll
            for (int jj = 0; jj < 4; ++jj)
                qf[jj] = r < 4 ? lds128(sb + SM_Q + r * 256 + (jj * 4 + c) * 16) : make_uint4(0u, 0u, 0u, 0u);
            const int ks_ = ST_K + warp;
            mbar_wait(bars + full_of(ks_), par_of(ks_));
            if (warp == 7) TS(13);
            const uint32_t ka = sb + slot_of(ks_) + r * 512 + c * 16;
#pragma unroll
            for (int T = 0; T < 2; ++T)
#pragma unroll
                for (int jj = 0; jj < 4; ++jj) {
                    const uint4 lo = lds128(ka + T * 4096 + jj * 64);
                    const uint4 hi = lds128(ka + T * 4096 + 256 + jj * 64);
                    mma16816(sacc[T], lo.x, hi.x, lo.y, hi.y, qf[jj].x, qf[jj].y);
                    mma16816(sacc[T], lo.z, hi.z, lo.w, hi.w, qf[jj].z, qf[jj].w);
                }
            __syncwarp();
            if (lane == 0) mbar_arrive(bars + empty_of(ks_), 8);
        }
        {
            float mx0 = fmaxf(fmaxf(sacc[0][0], sacc[0][2]), fmaxf(sacc[1][0], sacc[1][2]));
            float mx1 = fmaxf(fmaxf(sacc[0][1], sacc[0][3]), fmaxf(sacc[1][1], sacc[1][3]));
#pragma unroll
            for (int o = 4; o < 32; o <<= 1) {
                mx0 = fmaxf(mx0, __shfl_xor_sync(0xffffffffu, mx0, o));
                mx1 = fmaxf(mx1, __shfl_xor_sync(0xffffffffu, mx1, o));
            }
            if (lane < 2) {
                sts32(sb + SM_WMAX + ((2 * c) * 8 + warp) * 4, __float_as_uint(mx0));
                sts32(sb + SM_WMAX + ((2 * c + 1) * 8 + warp) * 4, __float_as_uint(mx1));
            }
            cbar();
            if (c < 2) {
                const uint32_t a = sb + SM_WMAX + c * 64;
                const uint4 u0 = lds128(a), u1 = lds128(a + 16), u2 = lds128(a + 32), u3 = lds128(a + 48);
#define MX4(u) fmaxf(fmaxf(__uint_as_float(u.x), __uint_as_float(u.y)), fmaxf(__uint_as_float(u.z), __uint_as_float(u.w)))
                mx0 = fmaxf(MX4(u0), MX4(u1));
                mx1 = fmaxf(MX4(u2), MX4(u3));
            }
            float l0 = 0.f, l1 = 0.f;
#pragma unroll
            for (int T = 0; T < 2; ++T) {
                const uint32_t p0 = pack_bf16(ex2((sacc[T][0] - mx0) * SC), ex2((sacc[T][2] - mx0) * SC));
                const uint32_t p1 = pack_bf16(ex2((sacc[T][1] - mx1) * SC), ex2((sacc[T][3] - mx1) * SC));
                l0 += bf_lo(p0) + bf_hi(p0);
                l1 += bf_lo(p1) + bf_hi(p1);
                if (c < 2) {
                    const uint32_t a = sb + SM_P + ((warp * 4 + 2 * c) * 4 + (r & 3)) * 16 + T * 8 + (r >> 2) * 4;
                    sts32(a, p0);
                    sts32(a + 64, p1);
                }
            }
#pragma unroll
            for (int o = 4; o < 32; o <<= 1) {
                l0 += __shfl_xor_sync(0xffffffffu, l0, o);
                l1 += __shfl_xor_sync(0xffffffffu, l1, o);
            }
            if (lane < 2) {
                sts32(sb + SM_WSUM + ((2 * c) * 8 + warp) * 4, __float_as_uint(l0));
                sts32(sb + SM_WSUM + ((2 * c + 1) * 8 + warp) * 4, __float_as_uint(l1));
            }
            cbar();
            if (warp == 1 && lane < 8) {
                const int hh = lane >> 1;
                const uint4 u0 = lds128(sb + SM_WMAX + hh * 32), u1 = lds128(sb + SM_WMAX + hh * 32 + 16);
                const uint4 s0 = lds128(sb + SM_WSUM + hh * 32), s1 = lds128(sb + SM_WSUM + hh * 32 + 16);
                const float m = fmaxf(MX4(u0), MX4(u1));
                const float l = ((__uint_as_float(s0.x) + __uint_as_float(s0.y)) + (__uint_as_float(s0.z) + __uint_as_float(s0.w))) +
                                ((__uint_as_float(s1.x) + __uint_as_float(s1.y)) + (__uint_as_float(s1.z) + __uint_as_float(s1.w)));
                st_async2(mapa(sb + SM_ML + rank * 8, lane), m, l, mapa(bars + BAR_ML * 8, lane));
            }
#undef MX4
            if (warp == 0) TS(14);
        }
        {
            float oa[2][4] = {};
#pragma unroll
            for (int j = 0; j < 8; ++j) {
                const uint4 pf = r < 4 ? lds128(sb + SM_P + ((j * 4 + r) * 4 + c) * 16) : make_uint4(0u, 0u, 0u, 0u);
                mbar_wait(bars + full_of(ST_V + j), par_of(ST_V + j));
                if (warp == 0 && j == 0) TS(19);
                if (warp == 0 && j == 7) TS(20);
                ldt_mma(oa[0], va + slot_of(ST_V + j), pf.x, pf.y);
                ldt_mma(oa[1], va + slot_of(ST_V + j) + 2048, pf.z, pf.w);
                __syncwarp();
                if (lane == 0 && j < 4) mbar_arrive(bars + empty_of(ST_V + j), 1);
            }
            if (c < 2) {
                const uint32_t off = sb + SM_INO + rank * 256 + ((warp & 3) * 16 + r) * 4;
                const uint32_t rk0 = (2 * c) * 2 + (warp >> 2), rk1 = rk0 + 2;
                const uint32_t d0 = mapa(off, rk0), d1 = mapa(off, rk1);
                const uint32_t rb0 = mapa(bars + BAR_O * 8, rk0), rb1 = mapa(bars + BAR_O * 8, rk1);
                st_async1(d0,      __float_as_uint(oa[0][0] + oa[1][0]), rb0);
                st_async1(d1,      __float_as_uint(oa[0][1] + oa[1][1]), rb1);
                st_async1(d0 + 32, __float_as_uint(oa[0][2] + oa[1][2]), rb0);
                st_async1(d1 + 32, __float_as_uint(oa[0][3] + oa[1][3]), rb1);
            }
            if (warp == 0) TS(15);
        }
        auto ffn_up = [&]() {
            float ha[2][4] = {};
#pragma unroll
            for (int j = 0; j < 2; ++j) {
                mbar_wait(bars + full_of(ST_W1 + j), par_of(ST_W1 + j));
                ldt_mma(ha[0], va + slot_of(ST_W1 + j), xb[4 * j], xb[4 * j + 1]);
                ldt_mma(ha[1], va + slot_of(ST_W1 + j) + 2048, xb[4 * j + 2], xb[4 * j + 3]);
            }
            if (c == 0) {
                const uint32_t dst = mapa(sb + SM_INF + rank * 128 + r * 8, warp), rb = mapa(bars + BAR_F * 8, warp);
                st_async2(dst,      ha[0][0] + ha[1][0], ha[0][1] + ha[1][1], rb);
                st_async2(dst + 64, ha[0][2] + ha[1][2], ha[0][3] + ha[1][3], rb);
            }
        };
        if (ffn) ffn_up();
        if (warp == 0) TS(16);
        {
            float acc[2][4] = {};
            const uint32_t x0 = (uint32_t)(((mi & 1) ^ ((rr >> 1) & 3)) * 16);
            const uint32_t ra = sb + ((mi >> 1) * 8 + rr) * 64;
            for (int it = 0; it < SPIN_LIMIT; ++it) {
                const int m = missing(mo0, mo1, ma0, ma1);
                if (__all_sync(0xffffffffu, (m & 3) == 0)) break;
                take_round(mo0, mo1, ma0, ma1, ino, ina, m);
            }
            if (warp == 0) TS(4);
            if (pol) { clear16(ino); clear16(ino + 4); }
            const uint32_t bo[8] = {mo0.x, mo0.y, mo0.z, mo0.w, mo1.x, mo1.y, mo1.z, mo1.w};
            const int wst = ST_WO + (warp >> 1);
            mbar_wait(bars + full_of(wst), par_of(wst));
            if (warp == 7) TS(21);
            const uint32_t a = ra + slot_of(wst) + (warp & 1) * 4096;
#pragma unroll
            for (int ks = 0; ks < 4; ++ks) {
                const uint32_t b0 = r < 2 ? ~bo[2 * ks] : 0u, b1_ = r < 2 ? ~bo[2 * ks + 1] : 0u;
                ldt_mma(acc[0], a + ks * 1024 + x0, b0, b1_);
                ldt_mma(acc[1], a + ks * 1024 + (x0 ^ 32), b0, b1_);
            }
            if (warp < 7) {
                for (int it = 0; it < SPIN_LIMIT; ++it) {
                    const int m = missing(mo0, mo1, ma0, ma1);
                    if (__all_sync(0xffffffffu, m == 0)) break;
                    take_round(mo0, mo1, ma0, ma1, ino, ina, m);
                }
                if (warp == 0) TS(23);
                if (pol) { clear8(ina); clear8(ina + 112); }
#pragma unroll
                for (int st = 0; st < 2; ++st) {
                    const uint2 m2 = st ? ma1 : ma0;
                    const uint32_t b0 = r < 2 ? ~m2.x : 0u, b1_ = r < 2 ? ~m2.y : 0u;
                    mbar_wait(bars + full_of(ST_W2 + st), par_of(ST_W2 + st));
                    if (warp == 0 && st == 1) TS(22);
                    const uint32_t a2 = ra + slot_of(ST_W2 + st) + warp * 1024;
                    ldt_mma(acc[0], a2 + x0, b0, b1_);
                    ldt_mma(acc[1], a2 + (x0 ^ 32), b0, b1_);
                }
            }
            if (c == 0) {
                const uint32_t dst = mapa(sb + SM_R4 + (rank * 8 + warp) * 32, r), rb = mapa(bars + BAR_R4 * 8, r);
                st_async4(dst,      acc[0][0], acc[0][1], acc[0][2], acc[0][3], rb);
                st_async4(dst + 16, acc[1][0], acc[1][1], acc[1][2], acc[1][3], rb);
            }
            if (warp == 0) TS(18);
            if (warp == 7) TS(24);
        }
    }
}

typedef CUresult (*EncodeFn)(CUtensorMap*, CUtensorMapDataType, cuuint32_t, void*, const cuuint64_t*, const cuuint64_t*,
                             const cuuint32_t*, const cuuint32_t*, CUtensorMapInterleave, CUtensorMapSwizzle,
                             CUtensorMapL2promotion, CUtensorMapFloatOOBfill);

void make_map(EncodeFn fn, CUtensorMap* m, const void* base, uint64_t rows, uint64_t cols, uint32_t box_rows, uint32_t box_slabs) {
    const cuuint64_t dims[3] = {64, rows, cols / 64};
    const cuuint64_t strides[2] = {cols * 2, 128};
    const cuuint32_t box[3] = {64, box_rows, box_slabs};
    const cuuint32_t es[3] = {1, 1, 1};
    fn(m, CU_TENSOR_MAP_DATA_TYPE_BFLOAT16, 3, const_cast<void*>(base), dims, strides, box, es, CU_TENSOR_MAP_INTERLEAVE_NONE,
       CU_TENSOR_MAP_SWIZZLE_128B, CU_TENSOR_MAP_L2_PROMOTION_L2_128B, CU_TENSOR_MAP_FLOAT_OOB_FILL_NONE);
}

void make_map2(EncodeFn fn, CUtensorMap* m, const void* base, uint64_t rows, uint64_t cols, uint32_t box_rows, uint32_t box_cols) {
    const cuuint64_t dims[2] = {cols, rows};
    const cuuint64_t strides[1] = {cols * 2};
    const cuuint32_t box[2] = {box_cols, box_rows};
    const cuuint32_t es[2] = {1, 1};
    fn(m, CU_TENSOR_MAP_DATA_TYPE_BFLOAT16, 2, const_cast<void*>(base), dims, strides, box, es, CU_TENSOR_MAP_INTERLEAVE_NONE,
       box_cols == 32 ? CU_TENSOR_MAP_SWIZZLE_64B : CU_TENSOR_MAP_SWIZZLE_128B, box_cols == 32 ? WPROMO : QPROMO,
       CU_TENSOR_MAP_FLOAT_OOB_FILL_NONE);
}

}

extern "C" void kernel_launch(void* const* d_in, const int* in_sizes, int n_in, void* d_out, int out_size) {
    (void)in_sizes; (void)n_in; (void)out_size;
    static EncodeFn encode = nullptr;
    static CUtensorMap maps[5];
    static const void* cached[5] = {nullptr, nullptr, nullptr, nullptr, nullptr};
    if (!encode) {
        void* fn = nullptr;
        cudaDriverEntryPointQueryResult st;
        cudaGetDriverEntryPoint("cuTensorMapEncodeTiled", &fn, cudaEnableDefault, &st);
        encode = (EncodeFn)fn;
        cudaFuncSetAttribute(fused_decode_kernel, cudaFuncAttributeMaxDynamicSharedMemorySize, SM_TOTAL);
    }
    if (cached[0] != d_in[3] || cached[1] != d_in[2] || cached[2] != d_in[6] || cached[3] != d_in[4] || cached[4] != d_in[8]) {
        make_map2(encode, &maps[0], d_in[3], 512, 4096, 64, 64);
        make_map(encode, &maps[1], d_in[2], 2 * 8 * 8192, 128, 32, 2);
        make_map(encode, &maps[2], d_in[6], 512, 1792, 32, 2);
        make_map2(encode, &maps[3], d_in[4], 4096, 512, 128, 32);
        make_map2(encode, &maps[4], d_in[8], 1792, 512, 112, 32);
        cached[0] = d_in[3]; cached[1] = d_in[2]; cached[2] = d_in[6]; cached[3] = d_in[4]; cached[4] = d_in[8];
    }
    cudaLaunchConfig_t cfg = {};
    cfg.gridDim = dim3(NCTA);
    cfg.blockDim = dim3(NTHREADS);
    cfg.dynamicSmemBytes = SM_TOTAL;
    cfg.stream = cudaStreamPerThread;
    cudaLaunchAttribute at[1];
    at[0].id = cudaLaunchAttributeClusterDimension;
    at[0].val.clusterDim.x = CLUSTER; at[0].val.clusterDim.y = 1; at[0].val.clusterDim.z = 1;
    cfg.attrs = at; cfg.numAttrs = 1;
    cudaLaunchKernelEx(&cfg, fused_decode_kernel, maps[0], maps[1], maps[2], maps[3], maps[4],
                       (const __nv_bfloat16*)d_in[0], (const __nv_bfloat16*)d_in[1],
                       (const __nv_bfloat16*)d_in[7], (__nv_bfloat16*)d_out);
}
```

```cpp
#include <cuda_runtime.h>
#include <cuda_bf16.h>
#include <cuda.h>
#include <stdint.h>

namespace {

constexpr int NCTA     = 128;
constexpr int CLUSTER  = 8;
constexpr int NFFN     = 112;
constexpr int NTHREADS = 352;
constexpr int SPIN_LIMIT = 1 << 22;
constexpr int PACE   = 660;
constexpr int LEAD8  = 32;
constexpr int WMIN   = 4;
constexpr int LEADB8 = 16;
constexpr int WB     = 3;

__device__ __align__(128) unsigned g_xo[2 * 128 * 32];
__device__ __align__(128) unsigned g_xa[2 * 112 * 16];
__device__ unsigned g_epoch;

constexpr int NSLOT   = 12;
constexpr int NSTAGE  = 32;
constexpr int ST_K = 8, ST_W1 = 16, ST_V = 18, ST_WO = 26, ST_W2 = 30;
constexpr int SM_QP   = NSLOT * 8192;
constexpr int SM_R4   = SM_QP;
constexpr int SM_Q    = SM_QP + 4096;
constexpr int SM_INO  = SM_Q + 1024;
constexpr int SM_INF  = SM_INO + 2048;
constexpr int SM_P    = SM_INF + 1024;
constexpr int SM_ML   = SM_P + 2048;
constexpr int SM_WMAX = SM_ML + 64;
constexpr int SM_WSUM = SM_WMAX + 128;
constexpr int SM_XN   = SM_WSUM + 128;
constexpr int SM_PAR  = SM_XN + 256;
constexpr int SM_BAR  = SM_PAR + 64;
constexpr int BAR_FULL = 0, BAR_EMPTY = 12, BAR_QP = 24, BAR_Q = 25, BAR_ML = 26, BAR_O = 27, BAR_F = 28, BAR_R4 = 29, BAR_XN = 30;
constexpr int SM_TOTAL = SM_BAR + 32 * 8 + 1024;

__device__ __forceinline__ void mbar_init(uint32_t bar, uint32_t cnt) {
    asm volatile("mbarrier.init.shared::cta.b64 [%0], %1;" :: "r"(bar), "r"(cnt) : "memory");
}
__device__ __forceinline__ void mbar_expect_tx(uint32_t bar, uint32_t bytes) {
    asm volatile("mbarrier.arrive.expect_tx.shared::cta.b64 _, [%0], %1;" :: "r"(bar), "r"(bytes) : "memory");
}
__device__ __forceinline__ void mbar_arrive(uint32_t bar, uint32_t cnt) {
    asm volatile("mbarrier.arrive.shared::cta.b64 _, [%0], %1;" :: "r"(bar), "r"(cnt) : "memory");
}
__device__ __forceinline__ bool mbar_try(uint32_t bar, uint32_t parity) {
    uint32_t ok;
    asm volatile("{\n .reg .pred p;\n mbarrier.try_wait.parity.shared::cta.b64 p, [%1], %2;\n selp.u32 %0, 1, 0, p;\n}"
                 : "=r"(ok) : "r"(bar), "r"(parity) : "memory");
    return ok != 0;
}
__device__ __forceinline__ bool mbar_test(uint32_t bar, uint32_t parity) {
    uint32_t ok;
    asm volatile("{\n .reg .pred p;\n mbarrier.test_wait.parity.shared::cta.b64 p, [%1], %2;\n selp.u32 %0, 1, 0, p;\n}"
                 : "=r"(ok) : "r"(bar), "r"(parity) : "memory");
    return ok != 0;
}
__device__ __forceinline__ void mbar_wait(uint32_t bar, uint32_t parity) {
    if (mbar_try(bar, parity)) return;
#pragma unroll 1
    for (int it = 0; it < SPIN_LIMIT; ++it)
        if (mbar_try(bar, parity)) return;
}
__device__ __forceinline__ void bulk_load(uint32_t dst, const void* src, uint32_t bytes, uint32_t bar) {
    asm volatile("cp.async.bulk.shared::cluster.global.mbarrier::complete_tx::bytes [%0], [%1], %2, [%3];"
                 :: "r"(dst), "l"(src), "r"(bytes), "r"(bar) : "memory");
}
__device__ __forceinline__ void tma3d(uint32_t dst, const CUtensorMap* map, int c1, int c2, uint32_t bar) {
    asm volatile("cp.async.bulk.tensor.3d.shared::cluster.global.mbarrier::complete_tx::bytes [%0], [%1, {%3, %4, %5}], [%2];"
                 :: "r"(dst), "l"(map), "r"(bar), "r"(0), "r"(c1), "r"(c2) : "memory");
}
__device__ __forceinline__ void tma2d(uint32_t dst, const CUtensorMap* map, int c0, int c1, uint32_t bar) {
    asm volatile("cp.async.bulk.tensor.2d.shared::cluster.global.mbarrier::complete_tx::bytes [%0], [%1, {%3, %4}], [%2];"
                 :: "r"(dst), "l"(map), "r"(bar), "r"(c0), "r"(c1) : "memory");
}
__device__ __forceinline__ uint32_t mapa(uint32_t a, uint32_t rank) {
    uint32_t d;
    asm("mapa.shared::cluster.u32 %0, %1, %2;" : "=r"(d) : "r"(a), "r"(rank));
    return d;
}
__device__ __forceinline__ void st_async1(uint32_t dst, uint32_t v, uint32_t bar) {
    asm volatile("st.async.shared::cluster.mbarrier::complete_tx::bytes.b32 [%0], %1, [%2];"
                 :: "r"(dst), "r"(v), "r"(bar) : "memory");
}
__device__ __forceinline__ void st_async2(uint32_t dst, float a, float b, uint32_t bar) {
    asm volatile("st.async.shared::cluster.mbarrier::complete_tx::bytes.v2.f32 [%0], {%1,%2}, [%3];"
                 :: "r"(dst), "f"(a), "f"(b), "r"(bar) : "memory");
}
__device__ __forceinline__ void st_async4(uint32_t dst, float a, float b, float c, float d, uint32_t bar) {
    asm volatile("st.async.shared::cluster.mbarrier::complete_tx::bytes.v4.f32 [%0], {%1,%2,%3,%4}, [%5];"
                 :: "r"(dst), "f"(a), "f"(b), "f"(c), "f"(d), "r"(bar) : "memory");
}
__device__ __forceinline__ void put8(void* p, unsigned a, unsigned b) {
    asm volatile("{\n .reg .b64 v;\n mov.b64 v, {%1,%2};\n red.relaxed.gpu.global.or.b64 [%0], v;\n}"
                 :: "l"(p), "r"(a), "r"(b) : "memory");
}
__device__ __forceinline__ void clear16(void* p) {
    asm volatile("st.relaxed.gpu.global.v4.u32 [%0], {%1,%1,%1,%1};" :: "l"(p), "r"(0u) : "memory");
}
__device__ __forceinline__ void poll2(uint2& a, uint2& b, const void* pa, const void* pb, int ma, int mb) {
    asm volatile("{\n .reg .pred p, q;\n setp.ne.s32 p, %6, 0;\n setp.ne.s32 q, %7, 0;\n"
                 " @p ld.relaxed.gpu.global.v2.u32 {%0,%1}, [%4];\n"
                 " @q ld.relaxed.gpu.global.v2.u32 {%2,%3}, [%5];\n}"
                 : "+r"(a.x), "+r"(a.y), "+r"(b.x), "+r"(b.y) : "l"(pa), "l"(pb), "r"(ma), "r"(mb) : "memory");
}
__device__ __forceinline__ void poll1(uint2& b, const void* pb, int mb) {
    asm volatile("{\n .reg .pred q;\n setp.ne.s32 q, %3, 0;\n @q ld.relaxed.gpu.global.v2.u32 {%0,%1}, [%2];\n}"
                 : "+r"(b.x), "+r"(b.y) : "l"(pb), "r"(mb) : "memory");
}
__device__ __forceinline__ bool nz2(const uint2& v) { return v.x != 0u && v.y != 0u; }
__device__ __forceinline__ unsigned enc(unsigned w) { return ~min(w, 0xFFFFFFFEu); }
__device__ __forceinline__ uint4 lds128(uint32_t a) {
    uint4 v;
    asm volatile("ld.shared.v4.u32 {%0,%1,%2,%3}, [%4];" : "=r"(v.x), "=r"(v.y), "=r"(v.z), "=r"(v.w) : "r"(a) : "memory");
    return v;
}
__device__ __forceinline__ float2 lds64f(uint32_t a) {
    float2 v;
    asm volatile("ld.shared.v2.f32 {%0,%1}, [%2];" : "=f"(v.x), "=f"(v.y) : "r"(a) : "memory");
    return v;
}
__device__ __forceinline__ uint32_t lds32(uint32_t a) {
    uint32_t v;
    asm volatile("ld.shared.u32 %0, [%1];" : "=r"(v) : "r"(a) : "memory");
    return v;
}
__device__ __forceinline__ void sts32(uint32_t a, uint32_t v) {
    asm volatile("st.shared.u32 [%0], %1;" :: "r"(a), "r"(v) : "memory");
}
__device__ __forceinline__ void mma16816(float (&d)[4], uint32_t a0, uint32_t a1, uint32_t a2, uint32_t a3,
                                         uint32_t b0, uint32_t b1) {
    asm volatile("mma.sync.aligned.m16n8k16.row.col.f32.bf16.bf16.f32 {%0,%1,%2,%3}, {%4,%5,%6,%7}, {%8,%9}, {%0,%1,%2,%3};"
                 : "+f"(d[0]), "+f"(d[1]), "+f"(d[2]), "+f"(d[3])
                 : "r"(a0), "r"(a1), "r"(a2), "r"(a3), "r"(b0), "r"(b1));
}
__device__ __forceinline__ void ldt_mma(float (&d)[4], uint32_t addr, uint32_t b0, uint32_t b1) {
    uint32_t a0, a1, a2, a3;
    asm volatile("ldmatrix.sync.aligned.m8n8.x4.trans.shared.b16 {%0,%1,%2,%3}, [%4];"
                 : "=r"(a0), "=r"(a1), "=r"(a2), "=r"(a3) : "r"(addr) : "memory");
    mma16816(d, a0, a1, a2, a3, b0, b1);
}
__device__ __forceinline__ uint32_t pack_bf16(float lo, float hi) {
    uint32_t r;
    asm("cvt.rn.bf16x2.f32 %0, %1, %2;" : "=r"(r) : "f"(hi), "f"(lo));
    return r;
}
__device__ __forceinline__ float bf_lo(uint32_t w) { return __uint_as_float(w << 16); }
__device__ __forceinline__ float bf_hi(uint32_t w) { return __uint_as_float(w & 0xFFFF0000u); }
__device__ __forceinline__ float ex2(float x) {
    float y;
    asm("ex2.approx.ftz.f32 %0, %1;" : "=f"(y) : "f"(x));
    return y;
}
__device__ __forceinline__ void cbar() { asm volatile("bar.sync 1, 256;" ::: "memory"); }

__host__ __device__ constexpr int cum8(int s) {
    return s <= 8 ? s * 4 : s <= 16 ? 32 + (s - 8) * 8 : s <= 18 ? 96 + (s - 16) * 7 : s <= 30 ? 110 + (s - 18) * 8 : 206 + (s - 30) * 7;
}
__device__ __forceinline__ uint32_t empty_of(int stage) { return (uint32_t)(BAR_EMPTY + stage % NSLOT) * 8u; }
__device__ __forceinline__ uint32_t slot_of(int stage) { return (uint32_t)(stage % NSLOT) * 8192u; }
__device__ __forceinline__ uint32_t full_of(int stage) { return (uint32_t)(BAR_FULL + stage % NSLOT) * 8u; }
__device__ __forceinline__ uint32_t par_of(int stage) { return (uint32_t)(stage / NSLOT) & 1u; }

__global__ void __launch_bounds__(NTHREADS, 2)
fused_decode_kernel(const __grid_constant__ CUtensorMap map_wq, const __grid_constant__ CUtensorMap map_v,
                    const __grid_constant__ CUtensorMap map_w1, const __grid_constant__ CUtensorMap map_wo,
                    const __grid_constant__ CUtensorMap map_w2,
                    const __nv_bfloat16* __restrict__ x, const __nv_bfloat16* __restrict__ kc,
                    const __nv_bfloat16* __restrict__ b1, __nv_bfloat16* __restrict__ out) {
    extern __shared__ unsigned char smem_raw[];
    const uint32_t sb = ((uint32_t)__cvta_generic_to_shared(smem_raw) + 1023u) & ~1023u;
    const uint32_t bars = sb + SM_BAR;
    const int tid = threadIdx.x, warp = tid >> 5, lane = tid & 31;
    const int cta = blockIdx.x;
    const int cl = cta >> 3, rank = cta & 7;
    const int b = cl >> 3, g = cl & 7;
    const int fcta = cta - 8;
    const bool ffn = fcta >= 0 && fcta < NFFN;
    const float SC = 0.08838834764831845f * 1.4426950408889634f;

    const int krow = cl * 8192 + 6144 + rank * 256;
    const char* ksrc = (const char*)(kc + (size_t)krow * 128);
    auto issue = [&](int s) {
        const uint32_t fb = bars + full_of(s), dst = sb + slot_of(s);
        if (!ffn && (s == ST_W1 || s == ST_W1 + 1)) {
            mbar_arrive(fb, 1);
        } else {
            mbar_expect_tx(fb, s >= ST_W2 ? 7168 : 8192);
            if (s < ST_W1)       bulk_load(dst, ksrc + (s - ST_K) * 8192, 8192, fb);
            else if (s < ST_V)   tma3d(dst, &map_w1, rank * 64 + (s - ST_W1) * 32, (cl - 1) * 2, fb);
            else if (s < ST_WO)  tma3d(dst, &map_v, krow + (s - ST_V) * 32, 0, fb);
            else if (s < ST_W2)  tma2d(dst, &map_wo, cl * 32, rank * 512 + (s - ST_WO) * 128, fb);
            else                 tma2d(dst, &map_w2, cl * 32, rank * 224 + (s - ST_W2) * 112, fb);
        }
    };

    if (warp == 8) {
        const uint32_t c0 = (uint32_t)clock();
        if (lane == 0) {
            asm volatile("cp.async.bulk.prefetch.L2.global [%0], %1;" :: "l"(ksrc), "r"(8192) : "memory");
#pragma unroll
            for (int s = ST_K; s < NSLOT; ++s) {
                mbar_init(bars + full_of(s), 1);
                if (s < ST_K + 1) issue(s);
            }
            asm volatile("prefetch.tensormap [%0];" :: "l"(&map_v) : "memory");
            asm volatile("prefetch.tensormap [%0];" :: "l"(&map_w1) : "memory");
            asm volatile("prefetch.tensormap [%0];" :: "l"(&map_wo) : "memory");
            asm volatile("prefetch.tensormap [%0];" :: "l"(&map_w2) : "memory");
        }
        __syncthreads();
        asm volatile("barrier.cluster.arrive.relaxed.aligned;" ::: "memory");
        if (lane == 0) {
#pragma unroll
            for (int s = ST_K; s < NSTAGE; ++s) {
                if (s < ST_K + 1) continue;
                if (s < ST_WO) {
#pragma unroll 1
                    for (int it = 0; it < SPIN_LIMIT; ++it) {
                        if ((int)((uint32_t)clock() - c0) >= (cum8(s) - LEAD8) * PACE / 8) break;
                        if (mbar_test(bars + full_of(s - WMIN), par_of(s - WMIN))) break;
                    }
                } else {
                    if (s == ST_WO) {
#pragma unroll
                        for (int k = ST_W1; k < s - WB; ++k) mbar_wait(bars + full_of(k), par_of(k));
                    }
#pragma unroll 1
                    for (int it = 0; it < SPIN_LIMIT; ++it) {
                        if ((int)((uint32_t)clock() - c0) >= (cum8(s) - LEADB8) * PACE / 8) break;
                        if (mbar_test(bars + full_of(s - WB), par_of(s - WB))) break;
                    }
                }
                if (s >= NSLOT) mbar_wait(bars + empty_of(s), par_of(s - NSLOT));
                issue(s);
            }
        }
    } else if (warp == 10) {
        __syncthreads();
        asm volatile("barrier.cluster.arrive.relaxed.aligned;" ::: "memory");
        {
            mbar_wait(bars + BAR_XN * 8, 0);
            const uint32_t par = lds32(sb + SM_PAR);
            unsigned* const xo = g_xo + (g * 8 + rank) * 64 + b * 32;
            if (lane < 8) clear16(xo + (par ^ 1u) * 4096 + lane * 4);
            unsigned* const dst = xo + par * 4096 + (lane & 3) * 8 + (lane >> 3) * 2;
            mbar_wait(bars + BAR_ML * 8, 0);
            float wn[8];
            {
                float m[8], l[8];
#pragma unroll
                for (int s = 0; s < 8; s += 2) {
                    const uint4 t = lds128(sb + SM_ML + s * 8);
                    m[s] = __uint_as_float(t.x); l[s] = __uint_as_float(t.y);
                    m[s + 1] = __uint_as_float(t.z); l[s + 1] = __uint_as_float(t.w);
                }
                const float M = fmaxf(fmaxf(fmaxf(m[0], m[1]), fmaxf(m[2], m[3])), fmaxf(fmaxf(m[4], m[5]), fmaxf(m[6], m[7])));
                float L = 0.f;
#pragma unroll
                for (int s = 0; s < 8; ++s) { wn[s] = ex2((m[s] - M) * SC); L = fmaf(wn[s], l[s], L); }
                const float inv = 1.f / L;
#pragma unroll
                for (int s = 0; s < 8; ++s) wn[s] *= inv;
            }
            mbar_wait(bars + BAR_O * 8, 0);
            float o0 = 0.f, o1 = 0.f;
#pragma unroll
            for (int s = 0; s < 8; ++s) {
                const float2 t = lds64f(sb + SM_INO + s * 256 + lane * 8);
                o0 = fmaf(wn[s], t.x, o0); o1 = fmaf(wn[s], t.y, o1);
            }
            const uint32_t ow = enc(pack_bf16(o0, o1));
            const uint32_t oh = __shfl_down_sync(0xffffffffu, ow, 4);
            if (!(lane & 4)) put8(dst, ow, oh);
        }
    } else if (warp == 9) {
        const uint4 xa0 = __ldg((const uint4*)(x + lane * 16));
        const uint4 xa1 = __ldg((const uint4*)(x + lane * 16 + 8));
        const uint4 xc0 = __ldg((const uint4*)(x + 512 + lane * 16));
        const uint4 xc1 = __ldg((const uint4*)(x + 512 + lane * 16 + 8));
        const uint32_t xr0 = __ldg((const unsigned*)(x + rank * 64) + lane);
        const uint32_t xr1 = __ldg((const unsigned*)(x + 512 + rank * 64) + lane);
        const int e = (lane & 3) * 4 + ((lane >> 2) & 1) * 2 + ((lane >> 3) & 1);
        const int obase = ((rank >> 1) & 1) * 512 + cl * 32 + (rank & 1) * 16;
        const float xres = __bfloat162float(x[obase + (e >> 1) + (e & 1) * 8]);
        float bias = 0.f;
        if (ffn) bias = __bfloat162float(b1[fcta * 16 + (lane & 15)]);
        unsigned epoch;
        asm volatile("ld.relaxed.gpu.global.u32 %0, [%1];" : "=r"(epoch) : "l"(&g_epoch) : "memory");
        if (lane == 0) {
            mbar_init(bars + BAR_XN * 8, 1);
            mbar_init(bars + BAR_QP * 8, 1); mbar_expect_tx(bars + BAR_QP * 8, 2048);
            mbar_init(bars + BAR_Q * 8, 1);  mbar_expect_tx(bars + BAR_Q * 8, 1024);
            mbar_init(bars + BAR_ML * 8, 1); mbar_expect_tx(bars + BAR_ML * 8, 64);
            asm volatile("fence.mbarrier_init.release.cluster;" ::: "memory");
        }
        __syncthreads();
        asm volatile("barrier.cluster.arrive.relaxed.aligned;" ::: "memory");
        {
            const uint32_t wa[8] = {xa0.x, xa0.y, xa0.z, xa0.w, xa1.x, xa1.y, xa1.z, xa1.w};
            const uint32_t wc[8] = {xc0.x, xc0.y, xc0.z, xc0.w, xc1.x, xc1.y, xc1.z, xc1.w};
            float s0 = 0.f, s1 = 0.f;
#pragma unroll
            for (int i = 0; i < 8; ++i) { s0 += bf_lo(wa[i]) + bf_hi(wa[i]); s1 += bf_lo(wc[i]) + bf_hi(wc[i]); }
#pragma unroll
            for (int o = 16; o; o >>= 1) { s0 += __shfl_xor_sync(0xffffffffu, s0, o); s1 += __shfl_xor_sync(0xffffffffu, s1, o); }
            const float m0 = s0 * (1.f / 512.f), m1 = s1 * (1.f / 512.f);
            float v0 = 0.f, v1 = 0.f;
#pragma unroll
            for (int i = 0; i < 8; ++i) {
                float d;
                d = bf_lo(wa[i]) - m0; v0 = fmaf(d, d, v0); d = bf_hi(wa[i]) - m0; v0 = fmaf(d, d, v0);
                d = bf_lo(wc[i]) - m1; v1 = fmaf(d, d, v1); d = bf_hi(wc[i]) - m1; v1 = fmaf(d, d, v1);
            }
#pragma unroll
            for (int o = 16; o; o >>= 1) { v0 += __shfl_xor_sync(0xffffffffu, v0, o); v1 += __shfl_xor_sync(0xffffffffu, v1, o); }
            const float r0 = rsqrtf(v0 * (1.f / 512.f) + 1e-5f), r1 = rsqrtf(v1 * (1.f / 512.f) + 1e-5f);
            sts32(sb + SM_XN + lane * 4,       pack_bf16((bf_lo(xr0) - m0) * r0, (bf_hi(xr0) - m0) * r0));
            sts32(sb + SM_XN + 128 + lane * 4, pack_bf16((bf_lo(xr1) - m1) * r1, (bf_hi(xr1) - m1) * r1));
            if (lane == 0) sts32(sb + SM_PAR, epoch & 1u);
            __syncwarp();
            if (lane == 0) mbar_arrive(bars + BAR_XN * 8, 1);
            if (ffn && lane < 4) clear16(g_xa + ((epoch & 1u) ^ 1u) * 1792 + fcta * 16 + lane * 4);
        }
        asm volatile("barrier.cluster.wait.acquire.aligned;" ::: "memory");
        {
            mbar_wait(bars + BAR_QP * 8, 0);
            const uint32_t a = sb + SM_QP + (((2 * lane) & 7) * 8 + (lane >> 2)) * 4;
            float q0 = 0.f, q1 = 0.f;
#pragma unroll
            for (int s = 0; s < 8; ++s) {
                q0 += __uint_as_float(lds32(a + s * 256));
                q1 += __uint_as_float(lds32(a + s * 256 + 32));
            }
            const uint32_t qw = pack_bf16(q0, q1);
#pragma unroll
            for (int d = 0; d < 8; ++d)
                st_async1(mapa(sb + SM_Q + rank * 128 + lane * 4, d), qw, mapa(bars + BAR_Q * 8, d));
        }
        if (ffn) {
            mbar_wait(bars + BAR_F * 8, 0);
            float h = bias;
#pragma unroll
            for (int s = 0; s < 8; ++s) h += __uint_as_float(lds32(sb + SM_INF + s * 128 + (lane & 15) * 8 + (lane >> 4) * 4));
            const float ee = __expf(-fabsf(h));
            const float num = h >= 0.f ? fmaf(2.f, ee, 1.f) : ee * (ee + 2.f);
            const float den = h >= 0.f ? fmaf(2.f * ee, ee, num) : num + 2.f;
            const float act = h * __fdividef(num, den);
            const uint32_t w = enc(pack_bf16(act, __shfl_down_sync(0xffffffffu, act, 1)));
            const uint32_t wh = __shfl_down_sync(0xffffffffu, w, 8);
            if (!(lane & 9)) put8(g_xa + (epoch & 1u) * 1792 + fcta * 16 + (lane >> 4) * 8 + (lane & 7), w, wh);
        }
        if (rank < 4) {
            mbar_wait(bars + BAR_R4 * 8, 0);
            float a0 = 0.f, a1 = 0.f, a2 = 0.f, a3 = 0.f;
#pragma unroll
            for (int i = 0; i < 8; ++i) {
                const uint4 t = lds128(sb + SM_R4 + i * 512 + lane * 16);
                a0 += __uint_as_float(t.x); a1 += __uint_as_float(t.y);
                a2 += __uint_as_float(t.z); a3 += __uint_as_float(t.w);
            }
            const bool h2 = lane & 4, h3 = lane & 8;
            float k0 = h2 ? a2 : a0, k1 = h2 ? a3 : a1;
            k0 += __shfl_xor_sync(0xffffffffu, h2 ? a0 : a2, 4);
            k1 += __shfl_xor_sync(0xffffffffu, h2 ? a1 : a3, 4);
            float r = h3 ? k1 : k0;
            r += __shfl_xor_sync(0xffffffffu, h3 ? k0 : k1, 8);
            r += __shfl_xor_sync(0xffffffffu, r, 16);
            r += xres;
            const uint32_t w = pack_bf16(r, __shfl_down_sync(0xffffffffu, r, 4));
            if (!(lane & 20)) *(uint32_t*)(out + obase + (lane & 3) * 2 + (lane & 8)) = w;
            if (cta == 0 && lane == 0) g_epoch = epoch + 1u;
        }
    } else {
        const int r = lane >> 2, c = lane & 3;
        const int mi = lane >> 3, rr = lane & 7;
        if (lane == 0) {
            mbar_init(bars + full_of(warp), 1);
            mbar_expect_tx(bars + full_of(warp), 8192);
            tma2d(sb + slot_of(warp), &map_wq, g * 512 + warp * 64, rank * 64, bars + full_of(warp));
            mbar_init(bars + (BAR_EMPTY + warp) * 8, 8);
            if (warp < 4) mbar_init(bars + (BAR_EMPTY + 8 + warp) * 8, 8);
            else if (warp < 7) {
                mbar_init(bars + (BAR_O + warp - 4) * 8, 1);
                mbar_expect_tx(bars + (BAR_O + warp - 4) * 8, warp == 4 ? 2048u : warp == 5 ? 1024u : 4096u);
            }
            asm volatile("fence.mbarrier_init.release.cluster;" ::: "memory");
        }
        __syncthreads();
        asm volatile("barrier.cluster.arrive.relaxed.aligned;" ::: "memory");
        const uint32_t va = sb + (warp >> 2) * 4096 + ((mi >> 1) * 8 + rr) * 128 + ((((2 * warp) & 7) + (mi & 1)) ^ rr) * 16;
        uint32_t xb[8];
        {
            mbar_wait(bars + BAR_XN * 8, 0);
#pragma unroll
            for (int i = 0; i < 8; ++i) xb[i] = r < 2 ? lds32(sb + SM_XN + r * 128 + (i * 4 + c) * 4) : 0u;
            float acc[4][4] = {};
            const uint32_t wa = sb + slot_of(warp) + ((mi >> 1) * 8 + rr) * 128;
            const uint32_t sw = (uint32_t)(((mi & 1) ^ rr) * 16);
            mbar_wait(bars + full_of(warp), 0);
#pragma unroll
            for (int ks = 0; ks < 4; ++ks)
#pragma unroll
                for (int t = 0; t < 4; ++t) ldt_mma(acc[t], wa + ks * 2048 + (sw ^ (t * 32)), xb[2 * ks], xb[2 * ks + 1]);
            __syncwarp();
            if (lane == 0) mbar_arrive(bars + empty_of(warp), 8);
            asm volatile("barrier.cluster.wait.acquire.aligned;" ::: "memory");
            if (c == 0) {
                const uint32_t dst = mapa(sb + SM_QP + rank * 256 + r * 32, warp), rb = mapa(bars + BAR_QP * 8, warp);
                st_async4(dst,      b ? acc[0][1] : acc[0][0], b ? acc[0][3] : acc[0][2], b ? acc[1][1] : acc[1][0], b ? acc[1][3] : acc[1][2], rb);
                st_async4(dst + 16, b ? acc[2][1] : acc[2][0], b ? acc[2][3] : acc[2][2], b ? acc[3][1] : acc[3][0], b ? acc[3][3] : acc[3][2], rb);
            }
        }
        const uint32_t par = lds32(sb + SM_PAR);
        const unsigned* const ino = g_xo + par * 4096 + (rank * 8 + warp) * 64 + lane * 2;
        const unsigned* const ina = g_xa + par * 1792 + (rank * 14 + (warp < 7 ? warp : 0) + (lane >> 3) * 7) * 16 + (lane & 7) * 2;
        const bool pola = lane < 16 && warp < 7;
        uint2 mo = make_uint2(0u, 0u), ma = mo;
        float sacc[2][4] = {};
        {
            mbar_wait(bars + BAR_Q * 8, 0);
            uint4 qf[4];
#pragma unroll
            for (int jj = 0; jj < 4; ++jj)
                qf[jj] = r < 4 ? lds128(sb + SM_Q + r * 256 + (jj * 4 + c) * 16) : make_uint4(0u, 0u, 0u, 0u);
            const int ks_ = ST_K + warp;
            mbar_wait(bars + full_of(ks_), par_of(ks_));
            const uint32_t ka = sb + slot_of(ks_) + r * 512 + c * 16;
#pragma unroll
            for (int T = 0; T < 2; ++T)
#pragma unroll
                for (int jj = 0; jj < 4; ++jj) {
                    const uint4 lo = lds128(ka + T * 4096 + jj * 64);
                    const uint4 hi = lds128(ka + T * 4096 + 256 + jj * 64);
                    mma16816(sacc[T], lo.x, hi.x, lo.y, hi.y, qf[jj].x, qf[jj].y);
                    mma16816(sacc[T], lo.z, hi.z, lo.w, hi.w, qf[jj].z, qf[jj].w);
                }
            __syncwarp();
            if (lane == 0) mbar_arrive(bars + empty_of(ks_), 8);
        }
        {
            float mx0 = fmaxf(fmaxf(sacc[0][0], sacc[0][2]), fmaxf(sacc[1][0], sacc[1][2]));
            float mx1 = fmaxf(fmaxf(sacc[0][1], sacc[0][3]), fmaxf(sacc[1][1], sacc[1][3]));
#pragma unroll
            for (int o = 4; o < 32; o <<= 1) {
                mx0 = fmaxf(mx0, __shfl_xor_sync(0xffffffffu, mx0, o));
                mx1 = fmaxf(mx1, __shfl_xor_sync(0xffffffffu, mx1, o));
            }
            if (lane < 2) {
                sts32(sb + SM_WMAX + ((2 * c) * 8 + warp) * 4, __float_as_uint(mx0));
                sts32(sb + SM_WMAX + ((2 * c + 1) * 8 + warp) * 4, __float_as_uint(mx1));
            }
            cbar();
            if (c < 2) {
                const uint32_t a = sb + SM_WMAX + c * 64;
                const uint4 u0 = lds128(a), u1 = lds128(a + 16), u2 = lds128(a + 32), u3 = lds128(a + 48);
#define MX4(u) fmaxf(fmaxf(__uint_as_float(u.x), __uint_as_float(u.y)), fmaxf(__uint_as_float(u.z), __uint_as_float(u.w)))
                mx0 = fmaxf(MX4(u0), MX4(u1));
                mx1 = fmaxf(MX4(u2), MX4(u3));
            }
            float l0 = 0.f, l1 = 0.f;
#pragma unroll
            for (int T = 0; T < 2; ++T) {
                const uint32_t p0 = pack_bf16(ex2((sacc[T][0] - mx0) * SC), ex2((sacc[T][2] - mx0) * SC));
                const uint32_t p1 = pack_bf16(ex2((sacc[T][1] - mx1) * SC), ex2((sacc[T][3] - mx1) * SC));
                l0 += bf_lo(p0) + bf_hi(p0);
                l1 += bf_lo(p1) + bf_hi(p1);
                if (c < 2) {
                    const uint32_t a = sb + SM_P + ((warp * 4 + 2 * c) * 4 + (r & 3)) * 16 + T * 8 + (r >> 2) * 4;
                    sts32(a, p0);
                    sts32(a + 64, p1);
                }
            }
#pragma unroll
            for (int o = 4; o < 32; o <<= 1) {
                l0 += __shfl_xor_sync(0xffffffffu, l0, o);
                l1 += __shfl_xor_sync(0xffffffffu, l1, o);
            }
            if (lane < 2) {
                sts32(sb + SM_WSUM + ((2 * c) * 8 + warp) * 4, __float_as_uint(l0));
                sts32(sb + SM_WSUM + ((2 * c + 1) * 8 + warp) * 4, __float_as_uint(l1));
            }
            cbar();
            if (warp == 1 && lane < 8) {
                const int hh = lane >> 1;
                const uint4 u0 = lds128(sb + SM_WMAX + hh * 32), u1 = lds128(sb + SM_WMAX + hh * 32 + 16);
                const uint4 s0 = lds128(sb + SM_WSUM + hh * 32), s1 = lds128(sb + SM_WSUM + hh * 32 + 16);
                const float m = fmaxf(MX4(u0), MX4(u1));
                const float l = ((__uint_as_float(s0.x) + __uint_as_float(s0.y)) + (__uint_as_float(s0.z) + __uint_as_float(s0.w))) +
                                ((__uint_as_float(s1.x) + __uint_as_float(s1.y)) + (__uint_as_float(s1.z) + __uint_as_float(s1.w)));
                st_async2(mapa(sb + SM_ML + rank * 8, lane), m, l, mapa(bars + BAR_ML * 8, lane));
            }
#undef MX4
        }
        {
            float ha[2][4] = {};
#pragma unroll
            for (int j = 0; j < 2; ++j) {
                mbar_wait(bars + full_of(ST_W1 + j), par_of(ST_W1 + j));
                if (ffn) {
                    ldt_mma(ha[0], va + slot_of(ST_W1 + j), xb[4 * j], xb[4 * j + 1]);
                    ldt_mma(ha[1], va + slot_of(ST_W1 + j) + 2048, xb[4 * j + 2], xb[4 * j + 3]);
                }
                __syncwarp();
                if (lane == 0) mbar_arrive(bars + empty_of(ST_W1 + j), 1);
            }
            if (ffn && c == 0) {
                const uint32_t dst = mapa(sb + SM_INF + rank * 128 + r * 8, warp), rb = mapa(bars + BAR_F * 8, warp);
                st_async2(dst,      ha[0][0] + ha[1][0], ha[0][1] + ha[1][1], rb);
                st_async2(dst + 64, ha[0][2] + ha[1][2], ha[0][3] + ha[1][3], rb);
            }
        }
        {
            float oa[2][4] = {};
#pragma unroll
            for (int j = 0; j < 8; ++j) {
                const uint4 pf = r < 4 ? lds128(sb + SM_P + ((j * 4 + r) * 4 + c) * 16) : make_uint4(0u, 0u, 0u, 0u);
                mbar_wait(bars + full_of(ST_V + j), par_of(ST_V + j));
                ldt_mma(oa[0], va + slot_of(ST_V + j), pf.x, pf.y);
                ldt_mma(oa[1], va + slot_of(ST_V + j) + 2048, pf.z, pf.w);
                __syncwarp();
                if (lane == 0 && ST_V + j < NSTAGE - NSLOT) mbar_arrive(bars + empty_of(ST_V + j), 1);
            }
            if (c < 2) {
                const uint32_t off = sb + SM_INO + rank * 256 + ((warp & 3) * 16 + r) * 4;
                const uint32_t rk0 = (2 * c) * 2 + (warp >> 2), rk1 = rk0 + 2;
                const uint32_t d0 = mapa(off, rk0), d1 = mapa(off, rk1);
                const uint32_t rb0 = mapa(bars + BAR_O * 8, rk0), rb1 = mapa(bars + BAR_O * 8, rk1);
                st_async1(d0,      __float_as_uint(oa[0][0] + oa[1][0]), rb0);
                st_async1(d1,      __float_as_uint(oa[0][1] + oa[1][1]), rb1);
                st_async1(d0 + 32, __float_as_uint(oa[0][2] + oa[1][2]), rb0);
                st_async1(d1 + 32, __float_as_uint(oa[0][3] + oa[1][3]), rb1);
            }
        }
        {
            float acc[2][4] = {};
            const uint32_t x0 = (uint32_t)(((mi & 1) ^ ((rr >> 1) & 3)) * 16);
            const uint32_t ra = sb + ((mi >> 1) * 8 + rr) * 64;
            uint32_t r4d[4], r4b[4];
#pragma unroll
            for (int k = 0; k < 4; ++k) { r4d[k] = mapa(sb + SM_R4 + (rank * 8 + warp) * 64 + r * 8, k); r4b[k] = mapa(bars + BAR_R4 * 8, k); }
#pragma unroll 1
            for (int it = 0; it < SPIN_LIMIT; ++it) {
                if (__all_sync(0xffffffffu, nz2(mo))) break;
                poll2(mo, ma, ino, ina, 1, pola && !nz2(ma));
            }
            poll1(ma, ina, pola && !nz2(ma));
            const int wst = ST_WO + (warp >> 1);
            const uint32_t a = ra + slot_of(wst) + (warp & 1) * 4096;
            uint32_t bo[8];
#pragma unroll
            for (int ks = 0; ks < 4; ++ks) {
                bo[2 * ks]     = ~__shfl_sync(0xffffffffu, mo.x, (lane & 7) * 4 + ks);
                bo[2 * ks + 1] = ~__shfl_sync(0xffffffffu, mo.y, (lane & 7) * 4 + ks);
            }
            mbar_wait(bars + full_of(wst), par_of(wst));
#pragma unroll
            for (int ks = 0; ks < 4; ++ks) {
                const uint32_t b0 = r < 2 ? bo[2 * ks] : 0u, b1_ = r < 2 ? bo[2 * ks + 1] : 0u;
                ldt_mma(acc[0], a + ks * 1024 + x0, b0, b1_);
                ldt_mma(acc[1], a + ks * 1024 + (x0 ^ 32), b0, b1_);
            }
            if (warp < 7) {
#pragma unroll 1
                for (int it = 0; it < SPIN_LIMIT; ++it) {
                    if (__all_sync(0xffffffffu, !pola || nz2(ma))) break;
                    poll1(ma, ina, pola);
                }
                const uint32_t hx = __shfl_down_sync(0xffffffffu, ma.x, 8), hy = __shfl_down_sync(0xffffffffu, ma.y, 8);
#pragma unroll
                for (int st = 0; st < 2; ++st) {
                    const uint32_t b0 = r < 2 ? ~(st ? hx : ma.x) : 0u, b1_ = r < 2 ? ~(st ? hy : ma.y) : 0u;
                    mbar_wait(bars + full_of(ST_W2 + st), par_of(ST_W2 + st));
                    const uint32_t a2 = ra + slot_of(ST_W2 + st) + warp * 1024;
                    ldt_mma(acc[0], a2 + x0, b0, b1_);
                    ldt_mma(acc[1], a2 + (x0 ^ 32), b0, b1_);
                }
            }
            if (c == 0) {
                st_async2(r4d[0], acc[0][0], acc[0][2], r4b[0]);
                st_async2(r4d[1], acc[1][0], acc[1][2], r4b[1]);
                st_async2(r4d[2], acc[0][1], acc[0][3], r4b[2]);
                st_async2(r4d[3], acc[1][1], acc[1][3], r4b[3]);
            }
        }
    }
}

typedef CUresult (*EncodeFn)(CUtensorMap*, CUtensorMapDataType, cuuint32_t, void*, const cuuint64_t*, const cuuint64_t*,
                             const cuuint32_t*, const cuuint32_t*, CUtensorMapInterleave, CUtensorMapSwizzle,
                             CUtensorMapL2promotion, CUtensorMapFloatOOBfill);

void make_map(EncodeFn fn, CUtensorMap* m, const void* base, uint64_t rows, uint64_t cols, uint32_t box_rows, uint32_t box_slabs) {
    const cuuint64_t dims[3] = {64, rows, cols / 64};
    const cuuint64_t strides[2] = {cols * 2, 128};
    const cuuint32_t box[3] = {64, box_rows, box_slabs};
    const cuuint32_t es[3] = {1, 1, 1};
    fn(m, CU_TENSOR_MAP_DATA_TYPE_BFLOAT16, 3, const_cast<void*>(base), dims, strides, box, es, CU_TENSOR_MAP_INTERLEAVE_NONE,
       CU_TENSOR_MAP_SWIZZLE_128B, CU_TENSOR_MAP_L2_PROMOTION_L2_128B, CU_TENSOR_MAP_FLOAT_OOB_FILL_NONE);
}

void make_map2(EncodeFn fn, CUtensorMap* m, const void* base, uint64_t rows, uint64_t cols, uint32_t box_rows, uint32_t box_cols) {
    const cuuint64_t dims[2] = {cols, rows};
    const cuuint64_t strides[1] = {cols * 2};
    const cuuint32_t box[2] = {box_cols, box_rows};
    const cuuint32_t es[2] = {1, 1};
    fn(m, CU_TENSOR_MAP_DATA_TYPE_BFLOAT16, 2, const_cast<void*>(base), dims, strides, box, es, CU_TENSOR_MAP_INTERLEAVE_NONE,
       box_cols == 32 ? CU_TENSOR_MAP_SWIZZLE_64B : CU_TENSOR_MAP_SWIZZLE_128B, box_cols == 32 ? CU_TENSOR_MAP_L2_PROMOTION_NONE : CU_TENSOR_MAP_L2_PROMOTION_L2_128B,
       CU_TENSOR_MAP_FLOAT_OOB_FILL_NONE);
}

}

extern "C" void kernel_launch(void* const* d_in, const int* in_sizes, int n_in, void* d_out, int out_size) {
    (void)in_sizes; (void)n_in; (void)out_size;
    static EncodeFn encode = nullptr;
    static CUtensorMap maps[5];
    static const void* cached[5] = {nullptr, nullptr, nullptr, nullptr, nullptr};
    if (!encode) {
        void* fn = nullptr;
        cudaDriverEntryPointQueryResult st;
        cudaGetDriverEntryPoint("cuTensorMapEncodeTiled", &fn, cudaEnableDefault, &st);
        encode = (EncodeFn)fn;
        cudaFuncSetAttribute(fused_decode_kernel, cudaFuncAttributeMaxDynamicSharedMemorySize, SM_TOTAL);
    }
    if (cached[0] != d_in[3] || cached[1] != d_in[2] || cached[2] != d_in[6] || cached[3] != d_in[4] || cached[4] != d_in[8]) {
        make_map2(encode, &maps[0], d_in[3], 512, 4096, 64, 64);
        make_map(encode, &maps[1], d_in[2], 2 * 8 * 8192, 128, 32, 2);
        make_map(encode, &maps[2], d_in[6], 512, 1792, 32, 2);
        make_map2(encode, &maps[3], d_in[4], 4096, 512, 128, 32);
        make_map2(encode, &maps[4], d_in[8], 1792, 512, 112, 32);
        cached[0] = d_in[3]; cached[1] = d_in[2]; cached[2] = d_in[6]; cached[3] = d_in[4]; cached[4] = d_in[8];
    }
    cudaLaunchConfig_t cfg = {};
    cfg.gridDim = dim3(NCTA);
    cfg.blockDim = dim3(NTHREADS);
    cfg.dynamicSmemBytes = SM_TOTAL;
    cfg.stream = cudaStreamPerThread;
    cudaLaunchAttribute at[1];
    at[0].id = cudaLaunchAttributeClusterDimension;
    at[0].val.clusterDim.x = CLUSTER; at[0].val.clusterDim.y = 1; at[0].val.clusterDim.z = 1;
    cfg.attrs = at; cfg.numAttrs = 1;
    cudaLaunchKernelEx(&cfg, fused_decode_kernel, maps[0], maps[1], maps[2], maps[3], maps[4],
                       (const __nv_bfloat16*)d_in[0], (const __nv_bfloat16*)d_in[1],
                       (const __nv_bfloat16*)d_in[7], (__nv_bfloat16*)d_out);
}
```

```cpp
#include <cuda_runtime.h>
#include <cuda_bf16.h>
#include <cuda.h>
#include <stdint.h>

namespace {

constexpr int NCTA     = 128;
constexpr int CLUSTER  = 8;
constexpr int NFFN     = 112;
constexpr int NTHREADS = 352;
constexpr int SPIN_LIMIT = 1 << 22;
constexpr int PACE   = 660;
constexpr int LEAD8  = 32;
constexpr int WMIN   = 4;
constexpr int LEADB8 = 16;
constexpr int WB     = 3;

__device__ __align__(128) unsigned g_xo[2 * 128 * 32];
__device__ __align__(128) unsigned g_xa[2 * 112 * 16];
__device__ unsigned g_epoch;

constexpr int NSLOT   = 12;
constexpr int NSTAGE  = 32;
constexpr int ST_K = 8, ST_W1 = 16, ST_V = 18, ST_WO = 26, ST_W2 = 30;
constexpr int SM_QP   = NSLOT * 8192;
constexpr int SM_R4   = SM_QP;
constexpr int SM_Q    = SM_QP + 4096;
constexpr int SM_INO  = SM_Q + 1024;
constexpr int SM_INF  = SM_INO + 2048;
constexpr int SM_P    = SM_INF + 1024;
constexpr int SM_ML   = SM_P + 2048;
constexpr int SM_WMAX = SM_ML + 64;
constexpr int SM_WSUM = SM_WMAX + 128;
constexpr int SM_XN   = SM_WSUM + 128;
constexpr int SM_PAR  = SM_XN + 256;
constexpr int SM_BAR  = SM_PAR + 64;
constexpr int BAR_FULL = 0, BAR_EMPTY = 12, BAR_QP = 24, BAR_Q = 25, BAR_ML = 26, BAR_O = 27, BAR_F = 28, BAR_R4 = 29, BAR_XN = 30;
constexpr int SM_TOTAL = SM_BAR + 32 * 8 + 1024;

__device__ __forceinline__ void mbar_init(uint32_t bar, uint32_t cnt) {
    asm volatile("mbarrier.init.shared::cta.b64 [%0], %1;" :: "r"(bar), "r"(cnt) : "memory");
}
__device__ __forceinline__ void mbar_expect_tx(uint32_t bar, uint32_t bytes) {
    asm volatile("mbarrier.arrive.expect_tx.shared::cta.b64 _, [%0], %1;" :: "r"(bar), "r"(bytes) : "memory");
}
__device__ __forceinline__ void mbar_arrive(uint32_t bar, uint32_t cnt) {
    asm volatile("mbarrier.arrive.shared::cta.b64 _, [%0], %1;" :: "r"(bar), "r"(cnt) : "memory");
}
__device__ __forceinline__ bool mbar_try(uint32_t bar, uint32_t parity) {
    uint32_t ok;
    asm volatile("{\n .reg .pred p;\n mbarrier.try_wait.parity.shared::cta.b64 p, [%1], %2;\n selp.u32 %0, 1, 0, p;\n}"
                 : "=r"(ok) : "r"(bar), "r"(parity) : "memory");
    return ok != 0;
}
__device__ __forceinline__ bool mbar_test(uint32_t bar, uint32_t parity) {
    uint32_t ok;
    asm volatile("{\n .reg .pred p;\n mbarrier.test_wait.parity.shared::cta.b64 p, [%1], %2;\n selp.u32 %0, 1, 0, p;\n}"
                 : "=r"(ok) : "r"(bar), "r"(parity) : "memory");
    return ok != 0;
}
__device__ __forceinline__ void mbar_wait(uint32_t bar, uint32_t parity) {
    if (mbar_try(bar, parity)) return;
#pragma unroll 1
    for (int it = 0; it < SPIN_LIMIT; ++it)
        if (mbar_try(bar, parity)) return;
}
__device__ __forceinline__ void bulk_load(uint32_t dst, const void* src, uint32_t bytes, uint32_t bar) {
    asm volatile("cp.async.bulk.shared::cluster.global.mbarrier::complete_tx::bytes [%0], [%1], %2, [%3];"
                 :: "r"(dst), "l"(src), "r"(bytes), "r"(bar) : "memory");
}
__device__ __forceinline__ void tma3d(uint32_t dst, const CUtensorMap* map, int c1, int c2, uint32_t bar) {
    asm volatile("cp.async.bulk.tensor.3d.shared::cluster.global.mbarrier::complete_tx::bytes [%0], [%1, {%3, %4, %5}], [%2];"
                 :: "r"(dst), "l"(map), "r"(bar), "r"(0), "r"(c1), "r"(c2) : "memory");
}
__device__ __forceinline__ void tma2d(uint32_t dst, const CUtensorMap* map, int c0, int c1, uint32_t bar) {
    asm volatile("cp.async.bulk.tensor.2d.shared::cluster.global.mbarrier::complete_tx::bytes [%0], [%1, {%3, %4}], [%2];"
                 :: "r"(dst), "l"(map), "r"(bar), "r"(c0), "r"(c1) : "memory");
}
__device__ __forceinline__ uint32_t mapa(uint32_t a, uint32_t rank) {
    uint32_t d;
    asm("mapa.shared::cluster.u32 %0, %1, %2;" : "=r"(d) : "r"(a), "r"(rank));
    return d;
}
__device__ __forceinline__ void st_async1(uint32_t dst, uint32_t v, uint32_t bar) {
    asm volatile("st.async.shared::cluster.mbarrier::complete_tx::bytes.b32 [%0], %1, [%2];"
                 :: "r"(dst), "r"(v), "r"(bar) : "memory");
}
__device__ __forceinline__ void st_async2(uint32_t dst, float a, float b, uint32_t bar) {
    asm volatile("st.async.shared::cluster.mbarrier::complete_tx::bytes.v2.f32 [%0], {%1,%2}, [%3];"
                 :: "r"(dst), "f"(a), "f"(b), "r"(bar) : "memory");
}
__device__ __forceinline__ void st_async4(uint32_t dst, float a, float b, float c, float d, uint32_t bar) {
    asm volatile("st.async.shared::cluster.mbarrier::complete_tx::bytes.v4.f32 [%0], {%1,%2,%3,%4}, [%5];"
                 :: "r"(dst), "f"(a), "f"(b), "f"(c), "f"(d), "r"(bar) : "memory");
}
__device__ __forceinline__ void put8(void* p, unsigned a, unsigned b) {
    asm volatile("{\n .reg .b64 v;\n mov.b64 v, {%1,%2};\n red.relaxed.gpu.global.or.b64 [%0], v;\n}"
                 :: "l"(p), "r"(a), "r"(b) : "memory");
}
__device__ __forceinline__ void clear16(void* p) {
    asm volatile("st.relaxed.gpu.global.v4.u32 [%0], {%1,%1,%1,%1};" :: "l"(p), "r"(0u) : "memory");
}
__device__ __forceinline__ void poll2(uint2& a, uint2& b, const void* pa, const void* pb, int ma, int mb) {
    asm volatile("{\n .reg .pred p, q;\n setp.ne.s32 p, %6, 0;\n setp.ne.s32 q, %7, 0;\n"
                 " @p ld.relaxed.gpu.global.v2.u32 {%0,%1}, [%4];\n"
                 " @q ld.relaxed.gpu.global.v2.u32 {%2,%3}, [%5];\n}"
                 : "+r"(a.x), "+r"(a.y), "+r"(b.x), "+r"(b.y) : "l"(pa), "l"(pb), "r"(ma), "r"(mb) : "memory");
}
__device__ __forceinline__ void poll1(uint2& b, const void* pb, int mb) {
    asm volatile("{\n .reg .pred q;\n setp.ne.s32 q, %3, 0;\n @q ld.relaxed.gpu.global.v2.u32 {%0,%1}, [%2];\n}"
                 : "+r"(b.x), "+r"(b.y) : "l"(pb), "r"(mb) : "memory");
}
__device__ __forceinline__ bool nz2(const uint2& v) { return v.x != 0u && v.y != 0u; }
__device__ __forceinline__ unsigned enc(unsigned w) { return ~min(w, 0xFFFFFFFEu); }
__device__ __forceinline__ uint4 lds128(uint32_t a) {
    uint4 v;
    asm volatile("ld.shared.v4.u32 {%0,%1,%2,%3}, [%4];" : "=r"(v.x), "=r"(v.y), "=r"(v.z), "=r"(v.w) : "r"(a) : "memory");
    return v;
}
__device__ __forceinline__ float2 lds64f(uint32_t a) {
    float2 v;
    asm volatile("ld.shared.v2.f32 {%0,%1}, [%2];" : "=f"(v.x), "=f"(v.y) : "r"(a) : "memory");
    return v;
}
__device__ __forceinline__ uint32_t lds32(uint32_t a) {
    uint32_t v;
    asm volatile("ld.shared.u32 %0, [%1];" : "=r"(v) : "r"(a) : "memory");
    return v;
}
__device__ __forceinline__ void sts32(uint32_t a, uint32_t v) {
    asm volatile("st.shared.u32 [%0], %1;" :: "r"(a), "r"(v) : "memory");
}
__device__ __forceinline__ void mma16816(float (&d)[4], uint32_t a0, uint32_t a1, uint32_t a2, uint32_t a3,
                                         uint32_t b0, uint32_t b1) {
    asm volatile("mma.sync.aligned.m16n8k16.row.col.f32.bf16.bf16.f32 {%0,%1,%2,%3}, {%4,%5,%6,%7}, {%8,%9}, {%0,%1,%2,%3};"
                 : "+f"(d[0]), "+f"(d[1]), "+f"(d[2]), "+f"(d[3])
                 : "r"(a0), "r"(a1), "r"(a2), "r"(a3), "r"(b0), "r"(b1));
}
__device__ __forceinline__ void ldt_mma(float (&d)[4], uint32_t addr, uint32_t b0, uint32_t b1) {
    uint32_t a0, a1, a2, a3;
    asm volatile("ldmatrix.sync.aligned.m8n8.x4.trans.shared.b16 {%0,%1,%2,%3}, [%4];"
                 : "=r"(a0), "=r"(a1), "=r"(a2), "=r"(a3) : "r"(addr) : "memory");
    mma16816(d, a0, a1, a2, a3, b0, b1);
}
__device__ __forceinline__ uint32_t pack_bf16(float lo, float hi) {
    uint32_t r;
    asm("cvt.rn.bf16x2.f32 %0, %1, %2;" : "=r"(r) : "f"(hi), "f"(lo));
    return r;
}
__device__ __forceinline__ float bf_lo(uint32_t w) { return __uint_as_float(w << 16); }
__device__ __forceinline__ float bf_hi(uint32_t w) { return __uint_as_float(w & 0xFFFF0000u); }
__device__ __forceinline__ float ex2(float x) {
    float y;
    asm("ex2.approx.ftz.f32 %0, %1;" : "=f"(y) : "f"(x));
    return y;
}
__device__ __forceinline__ void cbar() { asm volatile("bar.sync 1, 256;" ::: "memory"); }

__host__ __device__ constexpr int cum8(int s) {
    return s <= 8 ? s * 4 : s <= 16 ? 32 + (s - 8) * 8 : s <= 18 ? 96 + (s - 16) * 7 : s <= 30 ? 110 + (s - 18) * 8 : 206 + (s - 30) * 7;
}
__device__ __forceinline__ uint32_t empty_of(int stage) { return (uint32_t)(BAR_EMPTY + stage % NSLOT) * 8u; }
__device__ __forceinline__ uint32_t slot_of(int stage) { return (uint32_t)(stage % NSLOT) * 8192u; }
__device__ __forceinline__ uint32_t full_of(int stage) { return (uint32_t)(BAR_FULL + stage % NSLOT) * 8u; }
__device__ __forceinline__ uint32_t par_of(int stage) { return (uint32_t)(stage / NSLOT) & 1u; }

__global__ void __launch_bounds__(NTHREADS, 2)
fused_decode_kernel(const __grid_constant__ CUtensorMap map_wq, const __grid_constant__ CUtensorMap map_v,
                    const __grid_constant__ CUtensorMap map_w1, const __grid_constant__ CUtensorMap map_wo,
                    const __grid_constant__ CUtensorMap map_w2,
                    const __nv_bfloat16* __restrict__ x, const __nv_bfloat16* __restrict__ kc,
                    const __nv_bfloat16* __restrict__ b1, __nv_bfloat16* __restrict__ out) {
    extern __shared__ unsigned char smem_raw[];
    const uint32_t sb = ((uint32_t)__cvta_generic_to_shared(smem_raw) + 1023u) & ~1023u;
    const uint32_t bars = sb + SM_BAR;
    const int tid = threadIdx.x, warp = tid >> 5, lane = tid & 31;
    const int cta = blockIdx.x;
    const int cl = cta >> 3, rank = cta & 7;
    const int b = cl >> 3, g = cl & 7;
    const int fcta = cta - 8;
    const bool ffn = fcta >= 0 && fcta < NFFN;
    const float SC = 0.08838834764831845f * 1.4426950408889634f;

    const int krow = cl * 8192 + 6144 + rank * 256;
    const char* ksrc = (const char*)(kc + (size_t)krow * 128);
    auto issue = [&](int s) {
        const uint32_t fb = bars + full_of(s), dst = sb + slot_of(s);
        if (!ffn && (s == ST_W1 || s == ST_W1 + 1)) {
            mbar_arrive(fb, 1);
        } else {
            mbar_expect_tx(fb, s >= ST_W2 ? 7168 : 8192);
            if (s < ST_W1)       bulk_load(dst, ksrc + (s - ST_K) * 8192, 8192, fb);
            else if (s < ST_V)   tma3d(dst, &map_w1, rank * 64 + (s - ST_W1) * 32, (cl - 1) * 2, fb);
            else if (s < ST_WO)  tma3d(dst, &map_v, krow + (s - ST_V) * 32, 0, fb);
            else if (s < ST_W2)  tma2d(dst, &map_wo, cl * 32, rank * 512 + (s - ST_WO) * 128, fb);
            else                 tma2d(dst, &map_w2, cl * 32, rank * 224 + (s - ST_W2) * 112, fb);
        }
    };

    if (warp == 8) {
        const uint32_t c0 = (uint32_t)clock();
        if (lane == 0) {
            asm volatile("cp.async.bulk.prefetch.L2.global [%0], %1;" :: "l"(ksrc), "r"(8192) : "memory");
#pragma unroll
            for (int s = ST_K; s < NSLOT; ++s) {
                mbar_init(bars + full_of(s), 1);
                if (s == ST_K) issue(s);
            }
            asm volatile("prefetch.tensormap [%0];" :: "l"(&map_v) : "memory");
            asm volatile("prefetch.tensormap [%0];" :: "l"(&map_w1) : "memory");
            asm volatile("prefetch.tensormap [%0];" :: "l"(&map_wo) : "memory");
            asm volatile("prefetch.tensormap [%0];" :: "l"(&map_w2) : "memory");
        }
        __syncthreads();
        asm volatile("barrier.cluster.arrive.relaxed.aligned;" ::: "memory");
        if (lane == 0) {
#pragma unroll
            for (int s = ST_K + 1; s < NSTAGE; ++s) {
                if (s < ST_WO) {
#pragma unroll 1
                    for (int it = 0; it < SPIN_LIMIT; ++it) {
                        if ((int)((uint32_t)clock() - c0) >= (cum8(s) - LEAD8) * PACE / 8) break;
                        if (mbar_test(bars + full_of(s - WMIN), par_of(s - WMIN))) break;
                    }
                } else {
                    if (s == ST_WO) {
#pragma unroll
                        for (int k = ST_W1; k < s - WB; ++k) mbar_wait(bars + full_of(k), par_of(k));
                    }
#pragma unroll 1
                    for (int it = 0; it < SPIN_LIMIT; ++it) {
                        if ((int)((uint32_t)clock() - c0) >= (cum8(s) - LEADB8) * PACE / 8) break;
                        if (mbar_test(bars + full_of(s - WB), par_of(s - WB))) break;
                    }
                }
                if (s >= NSLOT) mbar_wait(bars + empty_of(s), par_of(s - NSLOT));
                issue(s);
            }
        }
    } else if (warp == 10) {
        __syncthreads();
        asm volatile("barrier.cluster.arrive.relaxed.aligned;" ::: "memory");
        {
            mbar_wait(bars + BAR_XN * 8, 0);
            const uint32_t par = lds32(sb + SM_PAR);
            unsigned* const xo = g_xo + (g * 8 + rank) * 64 + b * 32;
            if (lane < 8) clear16(xo + (par ^ 1u) * 4096 + lane * 4);
            unsigned* const dst = xo + par * 4096 + (lane & 3) * 8 + (lane >> 3) * 2;
            mbar_wait(bars + BAR_ML * 8, 0);
            float wn[8];
            {
                float m[8], l[8];
#pragma unroll
                for (int s = 0; s < 8; s += 2) {
                    const uint4 t = lds128(sb + SM_ML + s * 8);
                    m[s] = __uint_as_float(t.x); l[s] = __uint_as_float(t.y);
                    m[s + 1] = __uint_as_float(t.z); l[s + 1] = __uint_as_float(t.w);
                }
                const float M = fmaxf(fmaxf(fmaxf(m[0], m[1]), fmaxf(m[2], m[3])), fmaxf(fmaxf(m[4], m[5]), fmaxf(m[6], m[7])));
                float L = 0.f;
#pragma unroll
                for (int s = 0; s < 8; ++s) { wn[s] = ex2((m[s] - M) * SC); L = fmaf(wn[s], l[s], L); }
                const float inv = 1.f / L;
#pragma unroll
                for (int s = 0; s < 8; ++s) wn[s] *= inv;
            }
            mbar_wait(bars + BAR_O * 8, 0);
            float o0 = 0.f, o1 = 0.f;
#pragma unroll
            for (int s = 0; s < 8; ++s) {
                const float2 t = lds64f(sb + SM_INO + s * 256 + lane * 8);
                o0 = fmaf(wn[s], t.x, o0); o1 = fmaf(wn[s], t.y, o1);
            }
            const uint32_t ow = enc(pack_bf16(o0, o1));
            const uint32_t oh = __shfl_down_sync(0xffffffffu, ow, 4);
            if (!(lane & 4)) put8(dst, ow, oh);
        }
    } else if (warp == 9) {
        const uint4 xa0 = __ldg((const uint4*)(x + lane * 16));
        const uint4 xa1 = __ldg((const uint4*)(x + lane * 16 + 8));
        const uint4 xc0 = __ldg((const uint4*)(x + 512 + lane * 16));
        const uint4 xc1 = __ldg((const uint4*)(x + 512 + lane * 16 + 8));
        const uint32_t xr0 = __ldg((const unsigned*)(x + rank * 64) + lane);
        const uint32_t xr1 = __ldg((const unsigned*)(x + 512 + rank * 64) + lane);
        const int e = (lane & 3) * 4 + ((lane >> 2) & 1) * 2 + ((lane >> 3) & 1);
        const int obase = ((rank >> 1) & 1) * 512 + cl * 32 + (rank & 1) * 16;
        const float xres = __bfloat162float(x[obase + (e >> 1) + (e & 1) * 8]);
        float bias = 0.f;
        if (ffn) bias = __bfloat162float(b1[fcta * 16 + (lane & 15)]);
        unsigned epoch;
        asm volatile("ld.relaxed.gpu.global.u32 %0, [%1];" : "=r"(epoch) : "l"(&g_epoch) : "memory");
        if (lane == 0) {
            mbar_init(bars + BAR_XN * 8, 1);
            mbar_init(bars + BAR_QP * 8, 1); mbar_expect_tx(bars + BAR_QP * 8, 2048);
            mbar_init(bars + BAR_Q * 8, 1);  mbar_expect_tx(bars + BAR_Q * 8, 1024);
            mbar_init(bars + BAR_ML * 8, 1); mbar_expect_tx(bars + BAR_ML * 8, 64);
            asm volatile("fence.mbarrier_init.release.cluster;" ::: "memory");
        }
        __syncthreads();
        asm volatile("barrier.cluster.arrive.relaxed.aligned;" ::: "memory");
        {
            const uint32_t wa[8] = {xa0.x, xa0.y, xa0.z, xa0.w, xa1.x, xa1.y, xa1.z, xa1.w};
            const uint32_t wc[8] = {xc0.x, xc0.y, xc0.z, xc0.w, xc1.x, xc1.y, xc1.z, xc1.w};
            float s0 = 0.f, s1 = 0.f;
#pragma unroll
            for (int i = 0; i < 8; ++i) { s0 += bf_lo(wa[i]) + bf_hi(wa[i]); s1 += bf_lo(wc[i]) + bf_hi(wc[i]); }
#pragma unroll
            for (int o = 16; o; o >>= 1) { s0 += __shfl_xor_sync(0xffffffffu, s0, o); s1 += __shfl_xor_sync(0xffffffffu, s1, o); }
            const float m0 = s0 * (1.f / 512.f), m1 = s1 * (1.f / 512.f);
            float v0 = 0.f, v1 = 0.f;
#pragma unroll
            for (int i = 0; i < 8; ++i) {
                float d;
                d = bf_lo(wa[i]) - m0; v0 = fmaf(d, d, v0); d = bf_hi(wa[i]) - m0; v0 = fmaf(d, d, v0);
                d = bf_lo(wc[i]) - m1; v1 = fmaf(d, d, v1); d = bf_hi(wc[i]) - m1; v1 = fmaf(d, d, v1);
            }
#pragma unroll
            for (int o = 16; o; o >>= 1) { v0 += __shfl_xor_sync(0xffffffffu, v0, o); v1 += __shfl_xor_sync(0xffffffffu, v1, o); }
            const float r0 = rsqrtf(v0 * (1.f / 512.f) + 1e-5f), r1 = rsqrtf(v1 * (1.f / 512.f) + 1e-5f);
            sts32(sb + SM_XN + lane * 4,       pack_bf16((bf_lo(xr0) - m0) * r0, (bf_hi(xr0) - m0) * r0));
            sts32(sb + SM_XN + 128 + lane * 4, pack_bf16((bf_lo(xr1) - m1) * r1, (bf_hi(xr1) - m1) * r1));
            if (lane == 0) sts32(sb + SM_PAR, epoch & 1u);
            __syncwarp();
            if (lane == 0) mbar_arrive(bars + BAR_XN * 8, 1);
            if (ffn && lane < 4) clear16(g_xa + ((epoch & 1u) ^ 1u) * 1792 + fcta * 16 + lane * 4);
        }
        asm volatile("barrier.cluster.wait.acquire.aligned;" ::: "memory");
        {
            mbar_wait(bars + BAR_QP * 8, 0);
            const uint32_t a = sb + SM_QP + (((2 * lane) & 7) * 8 + (lane >> 2)) * 4;
            float q0 = 0.f, q1 = 0.f;
#pragma unroll
            for (int s = 0; s < 8; ++s) {
                q0 += __uint_as_float(lds32(a + s * 256));
                q1 += __uint_as_float(lds32(a + s * 256 + 32));
            }
            const uint32_t qw = pack_bf16(q0, q1);
#pragma unroll
            for (int d = 0; d < 8; ++d)
                st_async1(mapa(sb + SM_Q + rank * 128 + lane * 4, d), qw, mapa(bars + BAR_Q * 8, d));
        }
        if (ffn) {
            mbar_wait(bars + BAR_F * 8, 0);
            float h = bias;
#pragma unroll
            for (int s = 0; s < 8; ++s) h += __uint_as_float(lds32(sb + SM_INF + s * 128 + (lane & 15) * 8 + (lane >> 4) * 4));
            const float ee = __expf(-fabsf(h));
            const float num = h >= 0.f ? fmaf(2.f, ee, 1.f) : ee * (ee + 2.f);
            const float den = h >= 0.f ? fmaf(2.f * ee, ee, num) : num + 2.f;
            const float act = h * __fdividef(num, den);
            const uint32_t w = enc(pack_bf16(act, __shfl_down_sync(0xffffffffu, act, 1)));
            const uint32_t wh = __shfl_down_sync(0xffffffffu, w, 8);
            if (!(lane & 9)) put8(g_xa + (epoch & 1u) * 1792 + fcta * 16 + (lane >> 4) * 8 + (lane & 7), w, wh);
        }
        if (rank < 4) {
            mbar_wait(bars + BAR_R4 * 8, 0);
            float a0 = 0.f, a1 = 0.f, a2 = 0.f, a3 = 0.f;
#pragma unroll
            for (int i = 0; i < 8; ++i) {
                const uint4 t = lds128(sb + SM_R4 + i * 512 + lane * 16);
                a0 += __uint_as_float(t.x); a1 += __uint_as_float(t.y);
                a2 += __uint_as_float(t.z); a3 += __uint_as_float(t.w);
            }
            const bool h2 = lane & 4, h3 = lane & 8;
            float k0 = h2 ? a2 : a0, k1 = h2 ? a3 : a1;
            k0 += __shfl_xor_sync(0xffffffffu, h2 ? a0 : a2, 4);
            k1 += __shfl_xor_sync(0xffffffffu, h2 ? a1 : a3, 4);
            float r = h3 ? k1 : k0;
            r += __shfl_xor_sync(0xffffffffu, h3 ? k0 : k1, 8);
            r += __shfl_xor_sync(0xffffffffu, r, 16);
            r += xres;
            const uint32_t w = pack_bf16(r, __shfl_down_sync(0xffffffffu, r, 4));
            if (!(lane & 20)) *(uint32_t*)(out + obase + (lane & 3) * 2 + (lane & 8)) = w;
            if (cta == 0 && lane == 0) g_epoch = epoch + 1u;
        }
    } else {
        const int r = lane >> 2, c = lane & 3;
        const int mi = lane >> 3, rr = lane & 7;
        if (lane == 0) {
            mbar_init(bars + full_of(warp), 1);
            mbar_expect_tx(bars + full_of(warp), 8192);
            tma2d(sb + slot_of(warp), &map_wq, g * 512 + warp * 64, rank * 64, bars + full_of(warp));
            mbar_init(bars + (BAR_EMPTY + warp) * 8, 8);
            if (warp < 4) mbar_init(bars + (BAR_EMPTY + 8 + warp) * 8, 8);
            else if (warp < 7) {
                mbar_init(bars + (BAR_O + warp - 4) * 8, 1);
                mbar_expect_tx(bars + (BAR_O + warp - 4) * 8, warp == 4 ? 2048u : warp == 5 ? 1024u : 4096u);
            }
            asm volatile("fence.mbarrier_init.release.cluster;" ::: "memory");
        }
        __syncthreads();
        asm volatile("barrier.cluster.arrive.relaxed.aligned;" ::: "memory");
        const uint32_t va = sb + (warp >> 2) * 4096 + ((mi >> 1) * 8 + rr) * 128 + ((((2 * warp) & 7) + (mi & 1)) ^ rr) * 16;
        uint32_t xb[8];
        {
            mbar_wait(bars + BAR_XN * 8, 0);
#pragma unroll
            for (int i = 0; i < 8; ++i) xb[i] = r < 2 ? lds32(sb + SM_XN + r * 128 + (i * 4 + c) * 4) : 0u;
            float acc[4][4] = {};
            const uint32_t wa = sb + slot_of(warp) + ((mi >> 1) * 8 + rr) * 128;
            const uint32_t sw = (uint32_t)(((mi & 1) ^ rr) * 16);
            mbar_wait(bars + full_of(warp), 0);
#pragma unroll
            for (int ks = 0; ks < 4; ++ks)
#pragma unroll
                for (int t = 0; t < 4; ++t) ldt_mma(acc[t], wa + ks * 2048 + (sw ^ (t * 32)), xb[2 * ks], xb[2 * ks + 1]);
            __syncwarp();
            if (lane == 0) mbar_arrive(bars + empty_of(warp), 8);
            asm volatile("barrier.cluster.wait.acquire.aligned;" ::: "memory");
            if (c == 0) {
                const uint32_t dst = mapa(sb + SM_QP + rank * 256 + r * 32, warp), rb = mapa(bars + BAR_QP * 8, warp);
                st_async4(dst,      b ? acc[0][1] : acc[0][0], b ? acc[0][3] : acc[0][2], b ? acc[1][1] : acc[1][0], b ? acc[1][3] : acc[1][2], rb);
                st_async4(dst + 16, b ? acc[2][1] : acc[2][0], b ? acc[2][3] : acc[2][2], b ? acc[3][1] : acc[3][0], b ? acc[3][3] : acc[3][2], rb);
            }
        }
        const uint32_t par = lds32(sb + SM_PAR);
        const unsigned* const ino = g_xo + par * 4096 + (rank * 8 + warp) * 64 + lane * 2;
        const unsigned* const ina = g_xa + par * 1792 + (rank * 14 + (warp < 7 ? warp : 0) + (lane >> 3) * 7) * 16 + (lane & 7) * 2;
        const bool pola = lane < 16 && warp < 7;
        uint2 mo = make_uint2(0u, 0u), ma = mo;
        float sacc[2][4] = {};
        {
            mbar_wait(bars + BAR_Q * 8, 0);
            uint4 qf[4];
#pragma unroll
            for (int jj = 0; jj < 4; ++jj)
                qf[jj] = r < 4 ? lds128(sb + SM_Q + r * 256 + (jj * 4 + c) * 16) : make_uint4(0u, 0u, 0u, 0u);
            const int ks_ = ST_K + warp;
            mbar_wait(bars + full_of(ks_), par_of(ks_));
            const uint32_t ka = sb + slot_of(ks_) + r * 512 + c * 16;
#pragma unroll
            for (int T = 0; T < 2; ++T)
#pragma unroll
                for (int jj = 0; jj < 4; ++jj) {
                    const uint4 lo = lds128(ka + T * 4096 + jj * 64);
                    const uint4 hi = lds128(ka + T * 4096 + 256 + jj * 64);
                    mma16816(sacc[T], lo.x, hi.x, lo.y, hi.y, qf[jj].x, qf[jj].y);
                    mma16816(sacc[T], lo.z, hi.z, lo.w, hi.w, qf[jj].z, qf[jj].w);
                }
            __syncwarp();
            if (lane == 0) mbar_arrive(bars + empty_of(ks_), 8);
        }
        {
            float mx0 = fmaxf(fmaxf(sacc[0][0], sacc[0][2]), fmaxf(sacc[1][0], sacc[1][2]));
            float mx1 = fmaxf(fmaxf(sacc[0][1], sacc[0][3]), fmaxf(sacc[1][1], sacc[1][3]));
#pragma unroll
            for (int o = 4; o < 32; o <<= 1) {
                mx0 = fmaxf(mx0, __shfl_xor_sync(0xffffffffu, mx0, o));
                mx1 = fmaxf(mx1, __shfl_xor_sync(0xffffffffu, mx1, o));
            }
            if (lane < 2) {
                sts32(sb + SM_WMAX + ((2 * c) * 8 + warp) * 4, __float_as_uint(mx0));
                sts32(sb + SM_WMAX + ((2 * c + 1) * 8 + warp) * 4, __float_as_uint(mx1));
            }
            cbar();
            if (c < 2) {
                const uint32_t a = sb + SM_WMAX + c * 64;
                const uint4 u0 = lds128(a), u1 = lds128(a + 16), u2 = lds128(a + 32), u3 = lds128(a + 48);
#define MX4(u) fmaxf(fmaxf(__uint_as_float(u.x), __uint_as_float(u.y)), fmaxf(__uint_as_float(u.z), __uint_as_float(u.w)))
                mx0 = fmaxf(MX4(u0), MX4(u1));
                mx1 = fmaxf(MX4(u2), MX4(u3));
            }
            float l0 = 0.f, l1 = 0.f;
#pragma unroll
            for (int T = 0; T < 2; ++T) {
                const uint32_t p0 = pack_bf16(ex2((sacc[T][0] - mx0) * SC), ex2((sacc[T][2] - mx0) * SC));
                const uint32_t p1 = pack_bf16(ex2((sacc[T][1] - mx1) * SC), ex2((sacc[T][3] - mx1) * SC));
                l0 += bf_lo(p0) + bf_hi(p0);
                l1 += bf_lo(p1) + bf_hi(p1);
                if (c < 2) {
                    const uint32_t a = sb + SM_P + ((warp * 4 + 2 * c) * 4 + (r & 3)) * 16 + T * 8 + (r >> 2) * 4;
                    sts32(a, p0);
                    sts32(a + 64, p1);
                }
            }
#pragma unroll
            for (int o = 4; o < 32; o <<= 1) {
                l0 += __shfl_xor_sync(0xffffffffu, l0, o);
                l1 += __shfl_xor_sync(0xffffffffu, l1, o);
            }
            if (lane < 2) {
                sts32(sb + SM_WSUM + ((2 * c) * 8 + warp) * 4, __float_as_uint(l0));
                sts32(sb + SM_WSUM + ((2 * c + 1) * 8 + warp) * 4, __float_as_uint(l1));
            }
            cbar();
            if (warp == 1 && lane < 8) {
                const int hh = lane >> 1;
                const uint4 u0 = lds128(sb + SM_WMAX + hh * 32), u1 = lds128(sb + SM_WMAX + hh * 32 + 16);
                const uint4 s0 = lds128(sb + SM_WSUM + hh * 32), s1 = lds128(sb + SM_WSUM + hh * 32 + 16);
                const float m = fmaxf(MX4(u0), MX4(u1));
                const float l = ((__uint_as_float(s0.x) + __uint_as_float(s0.y)) + (__uint_as_float(s0.z) + __uint_as_float(s0.w))) +
                                ((__uint_as_float(s1.x) + __uint_as_float(s1.y)) + (__uint_as_float(s1.z) + __uint_as_float(s1.w)));
                st_async2(mapa(sb + SM_ML + rank * 8, lane), m, l, mapa(bars + BAR_ML * 8, lane));
            }
#undef MX4
        }
        {
            float ha[2][4] = {};
#pragma unroll
            for (int j = 0; j < 2; ++j) {
                mbar_wait(bars + full_of(ST_W1 + j), par_of(ST_W1 + j));
                if (ffn) {
                    ldt_mma(ha[0], va + slot_of(ST_W1 + j), xb[4 * j], xb[4 * j + 1]);
                    ldt_mma(ha[1], va + slot_of(ST_W1 + j) + 2048, xb[4 * j + 2], xb[4 * j + 3]);
                }
                __syncwarp();
                if (lane == 0) mbar_arrive(bars + empty_of(ST_W1 + j), 1);
            }
            if (ffn && c == 0) {
                const uint32_t dst = mapa(sb + SM_INF + rank * 128 + r * 8, warp), rb = mapa(bars + BAR_F * 8, warp);
                st_async2(dst,      ha[0][0] + ha[1][0], ha[0][1] + ha[1][1], rb);
                st_async2(dst + 64, ha[0][2] + ha[1][2], ha[0][3] + ha[1][3], rb);
            }
        }
        {
            float oa[2][4] = {};
#pragma unroll
            for (int j = 0; j < 8; ++j) {
                const uint4 pf = r < 4 ? lds128(sb + SM_P + ((j * 4 + r) * 4 + c) * 16) : make_uint4(0u, 0u, 0u, 0u);
                mbar_wait(bars + full_of(ST_V + j), par_of(ST_V + j));
                ldt_mma(oa[0], va + slot_of(ST_V + j), pf.x, pf.y);
                ldt_mma(oa[1], va + slot_of(ST_V + j) + 2048, pf.z, pf.w);
                __syncwarp();
                if (lane == 0 && ST_V + j < NSTAGE - NSLOT) mbar_arrive(bars + empty_of(ST_V + j), 1);
            }
            if (c < 2) {
                const uint32_t off = sb + SM_INO + rank * 256 + ((warp & 3) * 16 + r) * 4;
                const uint32_t rk0 = (2 * c) * 2 + (warp >> 2), rk1 = rk0 + 2;
                const uint32_t d0 = mapa(off, rk0), d1 = mapa(off, rk1);
                const uint32_t rb0 = mapa(bars + BAR_O * 8, rk0), rb1 = mapa(bars + BAR_O * 8, rk1);
                st_async1(d0,      __float_as_uint(oa[0][0] + oa[1][0]), rb0);
                st_async1(d1,      __float_as_uint(oa[0][1] + oa[1][1]), rb1);
                st_async1(d0 + 32, __float_as_uint(oa[0][2] + oa[1][2]), rb0);
                st_async1(d1 + 32, __float_as_uint(oa[0][3] + oa[1][3]), rb1);
            }
        }
        {
            float acc[2][4] = {};
            const uint32_t x0 = (uint32_t)(((mi & 1) ^ ((rr >> 1) & 3)) * 16);
            const uint32_t ra = sb + ((mi >> 1) * 8 + rr) * 64;
            uint32_t r4d[4], r4b[4];
#pragma unroll
            for (int k = 0; k < 4; ++k) { r4d[k] = mapa(sb + SM_R4 + (rank * 8 + warp) * 64 + r * 8, k); r4b[k] = mapa(bars + BAR_R4 * 8, k); }
#pragma unroll 1
            for (int it = 0; it < SPIN_LIMIT; ++it) {
                if (__all_sync(0xffffffffu, nz2(mo))) break;
                poll2(mo, ma, ino, ina, 1, pola && !nz2(ma));
            }
            poll1(ma, ina, pola && !nz2(ma));
            const int wst = ST_WO + (warp >> 1);
            const uint32_t a = ra + slot_of(wst) + (warp & 1) * 4096;
            uint32_t bo[8];
#pragma unroll
            for (int ks = 0; ks < 4; ++ks) {
                bo[2 * ks]     = ~__shfl_sync(0xffffffffu, mo.x, (lane & 7) * 4 + ks);
                bo[2 * ks + 1] = ~__shfl_sync(0xffffffffu, mo.y, (lane & 7) * 4 + ks);
            }
            mbar_wait(bars + full_of(wst), par_of(wst));
#pragma unroll
            for (int ks = 0; ks < 4; ++ks) {
                const uint32_t b0 = r < 2 ? bo[2 * ks] : 0u, b1_ = r < 2 ? bo[2 * ks + 1] : 0u;
                ldt_mma(acc[0], a + ks * 1024 + x0, b0, b1_);
                ldt_mma(acc[1], a + ks * 1024 + (x0 ^ 32), b0, b1_);
            }
            if (warp < 7) {
#pragma unroll 1
                for (int it = 0; it < SPIN_LIMIT; ++it) {
                    if (__all_sync(0xffffffffu, !pola || nz2(ma))) break;
                    poll1(ma, ina, pola);
                }
                const uint32_t hx = __shfl_down_sync(0xffffffffu, ma.x, 8), hy = __shfl_down_sync(0xffffffffu, ma.y, 8);
#pragma unroll
                for (int st = 0; st < 2; ++st) {
                    const uint32_t b0 = r < 2 ? ~(st ? hx : ma.x) : 0u, b1_ = r < 2 ? ~(st ? hy : ma.y) : 0u;
                    mbar_wait(bars + full_of(ST_W2 + st), par_of(ST_W2 + st));
                    const uint32_t a2 = ra + slot_of(ST_W2 + st) + warp * 1024;
                    ldt_mma(acc[0], a2 + x0, b0, b1_);
                    ldt_mma(acc[1], a2 + (x0 ^ 32), b0, b1_);
                }
            }
            if (c == 0) {
                st_async2(r4d[0], acc[0][0], acc[0][2], r4b[0]);
                st_async2(r4d[1], acc[1][0], acc[1][2], r4b[1]);
                st_async2(r4d[2], acc[0][1], acc[0][3], r4b[2]);
                st_async2(r4d[3], acc[1][1], acc[1][3], r4b[3]);
            }
        }
    }
}

typedef CUresult (*EncodeFn)(CUtensorMap*, CUtensorMapDataType, cuuint32_t, void*, const cuuint64_t*, const cuuint64_t*,
                             const cuuint32_t*, const cuuint32_t*, CUtensorMapInterleave, CUtensorMapSwizzle,
                             CUtensorMapL2promotion, CUtensorMapFloatOOBfill);

void make_map(EncodeFn fn, CUtensorMap* m, const void* base, uint64_t rows, uint64_t cols, uint32_t box_rows, uint32_t box_slabs) {
    const cuuint64_t dims[3] = {64, rows, cols / 64};
    const cuuint64_t strides[2] = {cols * 2, 128};
    const cuuint32_t box[3] = {64, box_rows, box_slabs};
    const cuuint32_t es[3] = {1, 1, 1};
    fn(m, CU_TENSOR_MAP_DATA_TYPE_BFLOAT16, 3, const_cast<void*>(base), dims, strides, box, es, CU_TENSOR_MAP_INTERLEAVE_NONE,
       CU_TENSOR_MAP_SWIZZLE_128B, CU_TENSOR_MAP_L2_PROMOTION_L2_256B, CU_TENSOR_MAP_FLOAT_OOB_FILL_NONE);
}

void make_map2(EncodeFn fn, CUtensorMap* m, const void* base, uint64_t rows, uint64_t cols, uint32_t box_rows, uint32_t box_cols) {
    const cuuint64_t dims[2] = {cols, rows};
    const cuuint64_t strides[1] = {cols * 2};
    const cuuint32_t box[2] = {box_cols, box_rows};
    const cuuint32_t es[2] = {1, 1};
    fn(m, CU_TENSOR_MAP_DATA_TYPE_BFLOAT16, 2, const_cast<void*>(base), dims, strides, box, es, CU_TENSOR_MAP_INTERLEAVE_NONE,
       box_cols == 32 ? CU_TENSOR_MAP_SWIZZLE_64B : CU_TENSOR_MAP_SWIZZLE_128B, box_cols == 32 ? CU_TENSOR_MAP_L2_PROMOTION_NONE : CU_TENSOR_MAP_L2_PROMOTION_L2_128B,
       CU_TENSOR_MAP_FLOAT_OOB_FILL_NONE);
}

}

extern "C" void kernel_launch(void* const* d_in, const int* in_sizes, int n_in, void* d_out, int out_size) {
    (void)in_sizes; (void)n_in; (void)out_size;
    static EncodeFn encode = nullptr;
    static CUtensorMap maps[5];
    static const void* cached[5] = {nullptr, nullptr, nullptr, nullptr, nullptr};
    if (!encode) {
        void* fn = nullptr;
        cudaDriverEntryPointQueryResult st;
        cudaGetDriverEntryPoint("cuTensorMapEncodeTiled", &fn, cudaEnableDefault, &st);
        encode = (EncodeFn)fn;
        cudaFuncSetAttribute(fused_decode_kernel, cudaFuncAttributeMaxDynamicSharedMemorySize, SM_TOTAL);
    }
    if (cached[0] != d_in[3] || cached[1] != d_in[2] || cached[2] != d_in[6] || cached[3] != d_in[4] || cached[4] != d_in[8]) {
        make_map2(encode, &maps[0], d_in[3], 512, 4096, 64, 64);
        make_map(encode, &maps[1], d_in[2], 2 * 8 * 8192, 128, 32, 2);
        make_map(encode, &maps[2], d_in[6], 512, 1792, 32, 2);
        make_map2(encode, &maps[3], d_in[4], 4096, 512, 128, 32);
        make_map2(encode, &maps[4], d_in[8], 1792, 512, 112, 32);
        cached[0] = d_in[3]; cached[1] = d_in[2]; cached[2] = d_in[6]; cached[3] = d_in[4]; cached[4] = d_in[8];
    }
    cudaLaunchConfig_t cfg = {};
    cfg.gridDim = dim3(NCTA);
    cfg.blockDim = dim3(NTHREADS);
    cfg.dynamicSmemBytes = SM_TOTAL;
    cfg.stream = cudaStreamPerThread;
    cudaLaunchAttribute at[1];
    at[0].id = cudaLaunchAttributeClusterDimension;
    at[0].val.clusterDim.x = CLUSTER; at[0].val.clusterDim.y = 1; at[0].val.clusterDim.z = 1;
    cfg.attrs = at; cfg.numAttrs = 1;
    cudaLaunchKernelEx(&cfg, fused_decode_kernel, maps[0], maps[1], maps[2], maps[3], maps[4],
                       (const __nv_bfloat16*)d_in[0], (const __nv_bfloat16*)d_in[1],
                       (const __nv_bfloat16*)d_in[7], (__nv_bfloat16*)d_out);
}
```
